```python
import torch

def _softmax(x, axis=-1):
    return torch.softmax(x, dim=axis)
def _gelu(x):
    return torch.nn.functional.gelu(x, approximate="tanh")
def _silu(x):
    return torch.nn.functional.silu(x)
def _sigmoid(x):
    return torch.sigmoid(x)
def _layernorm(x, axis=-1, eps=1e-5):
    m = x.mean(dim=axis, keepdim=True)
    v = x.var(dim=axis, keepdim=True, unbiased=False)
    return (x - m) / torch.sqrt(v + eps)
def _scatter_add(tgt, idx, src, axis=0):
    return tgt.clone().index_add_(axis, idx, src)
def _segment_sum(src, seg, n):
    out = torch.zeros((n,) + src.shape[1:], dtype=src.dtype)
    return out.index_add_(0, seg, src)
def _pad(x, pw):
    flat = tuple(v for pair in reversed(pw) for v in pair)
    return torch.nn.functional.pad(x, flat)

kernel_name = 'standalone__kv_cache_quant_int4_int2_kv_with_per_channel_or_per_token_scales__decode'

def setup_inputs():

    _w = (lambda a: (lambda t: t.to(torch.bfloat16) if t.is_floating_point() else t)(torch.as_tensor(a)))
    B = 1
    Sq = 1
    Skv = 16384
    Hq = 32
    Hkv = 8
    Dh = 128
    bits = 3
    G = -1
    if G <= 0 or G >= Skv:
        G = max(1, Skv // 2)
    Skv = (Skv // G) * G
    ngk = Skv // G
    qmax = (1 << bits) - 1
    return {
        "q": _w((lambda *s: torch.randn(*s, dtype=torch.bfloat16) * 1.6)(B, Hq, Sq, Dh)),
        "qk": _w(torch.randint(0, qmax + 1, (B, Hkv, Skv, Dh)).to(torch.int32)),
        "qv": _w(torch.randint(0, qmax + 1, (B, Hkv, Skv, Dh)).to(torch.int32)),
        "k_scales": _w(torch.abs((lambda *s: torch.randn(*s, dtype=torch.bfloat16) * 1.6)(B, Hkv, ngk, Dh)) * 0.05 + 0.02),
        "k_zeros": _w((lambda *s: torch.randn(*s, dtype=torch.bfloat16) * 1.6)(B, Hkv, ngk, Dh) + float(qmax) / 2.0),
        "v_scales": _w(torch.abs((lambda *s: torch.randn(*s, dtype=torch.bfloat16) * 0.05)(B, Hkv, Skv, 1)) * 0.05 + 0.02),
        "v_zeros": _w((lambda *s: torch.randn(*s, dtype=torch.bfloat16) * 0.05)(B, Hkv, Skv, 1) + float(qmax) / 2.0),
    }

def reference(q, qk, qv, k_scales, k_zeros, v_scales, v_zeros):
    B, Hq, Sq, Dh = q.shape
    Hkv, Skv = qk.shape[1], qk.shape[2]
    ngk = k_scales.shape[2]
    G = Skv // ngk
    ks = (lambda x, n, axis: torch.repeat_interleave(x, n, dim=axis))(k_scales, G, axis=2)
    kz = (lambda x, n, axis: torch.repeat_interleave(x, n, dim=axis))(k_zeros, G, axis=2)
    k = ((lambda x, dt: x.to(dt))(qk, q.dtype) - kz) * ks
    v = ((lambda x, dt: x.to(dt))(qv, q.dtype) - v_zeros) * v_scales
    rep = Hq // Hkv
    if rep > 1:
        k = (lambda x, n, axis: torch.repeat_interleave(x, n, dim=axis))(k, rep, axis=1)
        v = (lambda x, n, axis: torch.repeat_interleave(x, n, dim=axis))(v, rep, axis=1)
    scale = float(Dh) ** -0.5
    logits = torch.einsum("bhqd,bhkd->bhqk", q, k) * scale
    p = _softmax(logits, axis=-1)
    o = torch.einsum("bhqk,bhkd->bhqd", p, v)
    return o
```

```cpp
#include <cuda_runtime.h>
#include <cuda_bf16.h>
#include <stdint.h>

namespace {

constexpr int HKV = 8;
constexpr int REP = 4;
constexpr int SKV = 16384;
constexpr int DH = 128;
constexpr int NGK = 2;
constexpr int CPH = 16;
constexpr int CHUNK_TOK = 32;
constexpr int CHUNK_BYTES = CHUNK_TOK * DH * 4;
constexpr int NCH = SKV / CHUNK_TOK / CPH;
constexpr int TOK_PER_CTA = NCH * CHUNK_TOK;
#define STAGES 6
#define INFLIGHT 4
constexpr int NCW = 8;
constexpr int NCT = NCW * 32;
constexpr int NTHREADS = NCT + 32;

constexpr int OFF_RING = 0;
constexpr int OFF_P = OFF_RING + STAGES * CHUNK_BYTES;
constexpr int OFF_RED = OFF_P + TOK_PER_CTA * REP * 4;
constexpr int OFF_QS = OFF_RED + NCW * REP * DH * 4;
constexpr int OFF_CG = OFF_QS + NGK * REP * DH * 4;
constexpr int OFF_WMAX = OFF_CG + NGK * REP * 4;
constexpr int OFF_WSUM = OFF_WMAX + NCW * REP * 4;
constexpr int OFF_WZ = OFF_WSUM + NCW * REP * 4;
constexpr int OFF_BAR = OFF_WZ + NCW * REP * 4;
constexpr int SMEM_BYTES = OFF_BAR + 2 * STAGES * 8;

__device__ __align__(128) uint32_t g_box_o[HKV][CPH][CPH][32];
__device__ __align__(128) uint2 g_box_s[HKV][CPH][CPH];

__device__ __forceinline__ uint32_t smem_u32(const void* p) { return (uint32_t)__cvta_generic_to_shared(p); }
__device__ __forceinline__ void mbar_init(uint32_t bar, uint32_t cnt) {
    asm volatile("mbarrier.init.shared::cta.b64 [%0], %1;" ::"r"(bar), "r"(cnt) : "memory");
}
__device__ __forceinline__ void mbar_expect_tx(uint32_t bar, uint32_t bytes) {
    asm volatile("mbarrier.arrive.expect_tx.shared::cta.b64 _, [%0], %1;" ::"r"(bar), "r"(bytes) : "memory");
}
__device__ __forceinline__ void mbar_arrive(uint32_t bar) {
    asm volatile("mbarrier.arrive.shared::cta.b64 _, [%0];" ::"r"(bar) : "memory");
}
__device__ __forceinline__ void mbar_wait(uint32_t bar, uint32_t parity) {
    uint32_t ok;
    int it = 0;
    do {
        asm volatile(
            "{\n.reg .pred p;\nmbarrier.try_wait.parity.shared::cta.b64 p, [%1], %2;\nselp.u32 %0, 1, 0, p;\n}"
            : "=r"(ok) : "r"(bar), "r"(parity) : "memory");
    } while (!ok && ++it < (1 << 20));
}
__device__ __forceinline__ void bulk_load(uint32_t dst, const void* src, uint32_t bytes, uint32_t bar) {
    asm volatile("cp.async.bulk.shared::cluster.global.mbarrier::complete_tx::bytes [%0], [%1], %2, [%3];"
                 ::"r"(dst), "l"(src), "r"(bytes), "r"(bar) : "memory");
}
__device__ __forceinline__ int4 lds_i4(uint32_t a) {
    int4 v;
    asm volatile("ld.shared.v4.s32 {%0,%1,%2,%3}, [%4];" : "=r"(v.x), "=r"(v.y), "=r"(v.z), "=r"(v.w) : "r"(a) : "memory");
    return v;
}
__device__ __forceinline__ float4 lds_f4(uint32_t a) {
    float4 v;
    asm volatile("ld.shared.v4.f32 {%0,%1,%2,%3}, [%4];" : "=f"(v.x), "=f"(v.y), "=f"(v.z), "=f"(v.w) : "r"(a) : "memory");
    return v;
}
__device__ __forceinline__ void consumer_bar() { asm volatile("bar.sync 1, %0;" ::"n"(NCT) : "memory"); }
__device__ __forceinline__ float ex2(float x) {
    float y;
    asm("ex2.approx.ftz.f32 %0, %1;" : "=f"(y) : "f"(x));
    return y;
}
__device__ __forceinline__ uint32_t box_enc(float v) {
    uint32_t b = ~__float_as_uint(v);
    return b == 0u ? 0x80000000u : b;
}
__device__ __forceinline__ float box_dec(uint32_t w) { return __uint_as_float(~w); }
__device__ __forceinline__ float bf2f(__nv_bfloat16 x) { return __bfloat162float(x); }

#define TSTAMP(i)

__global__ void __launch_bounds__(NTHREADS, 1)
kvq_decode_kernel(const __nv_bfloat16* __restrict__ q, const int* __restrict__ qk, const int* __restrict__ qv,
                  const __nv_bfloat16* __restrict__ k_scales, const __nv_bfloat16* __restrict__ k_zeros,
                  const __nv_bfloat16* __restrict__ v_scales, const __nv_bfloat16* __restrict__ v_zeros,
                  __nv_bfloat16* __restrict__ out) {
    extern __shared__ __align__(128) unsigned char smem[];
    const uint32_t sb = smem_u32(smem);
    const int tid = threadIdx.x;
    const int warp = tid >> 5, lane = tid & 31;
    const int g = blockIdx.x & (HKV - 1);
    const int r = blockIdx.x >> 3;
    const uint32_t bar_full = sb + OFF_BAR, bar_empty = bar_full + STAGES * 8;

    if (warp == NCW) {
        const size_t base = ((size_t)g * (SKV / CHUNK_TOK) + r) * CHUNK_BYTES;
        const char* ksrc = (const char*)qk + base;
        const char* vsrc = (const char*)qv + base;
        if (lane == 0) {
            TSTAMP(0);
#pragma unroll
            for (int s = 0; s < STAGES; s++) {
                mbar_init(bar_full + s * 8, 1);
                mbar_init(bar_empty + s * 8, NCW);
            }
            asm volatile("fence.mbarrier_init.release.cluster;" ::: "memory");
#pragma unroll
            for (int i = 0; i < INFLIGHT; i++) {
                mbar_expect_tx(bar_full + i * 8, CHUNK_BYTES);
                bulk_load(sb + OFF_RING + i * CHUNK_BYTES, ksrc + (size_t)i * CPH * CHUNK_BYTES, CHUNK_BYTES, bar_full + i * 8);
            }
        }
        __syncthreads();
        if (lane == 0) {
            int st = INFLIGHT % STAGES, ph = (INFLIGHT / STAGES) & 1;
            int tst = 0, tph = 0;
            for (int i = INFLIGHT; i < 2 * NCH; i++) {
                mbar_wait(bar_full + tst * 8, tph);
                if (i >= STAGES) mbar_wait(bar_empty + st * 8, ph ^ 1);
                const char* src = (i < NCH ? ksrc : vsrc) + (size_t)(i & (NCH - 1)) * CPH * CHUNK_BYTES;
                mbar_expect_tx(bar_full + st * 8, CHUNK_BYTES);
                bulk_load(sb + OFF_RING + st * CHUNK_BYTES, src, CHUNK_BYTES, bar_full + st * 8);
                if (++st == STAGES) { st = 0; ph ^= 1; }
                if (++tst == STAGES) { tst = 0; tph ^= 1; }
            }
            TSTAMP(1);
        }
        __syncwarp();
        uint2* bs = &g_box_s[g][r][lane & 15];
        uint32_t sm_, sl_;
        for (int it = 0; it < (1 << 20); it++) {
            asm volatile("ld.relaxed.gpu.global.v2.u32 {%0,%1}, [%2];" : "=r"(sm_), "=r"(sl_) : "l"(bs) : "memory");
            if (__all_sync(0xffffffffu, sm_ != 0u && sl_ != 0u)) break;
        }
        const float mj = box_dec(sm_), lj = box_dec(sl_);
        float M = mj;
#pragma unroll
        for (int o = 8; o > 0; o >>= 1) M = fmaxf(M, __shfl_xor_sync(0xffffffffu, M, o));
        float fj = ex2(mj - M);
        float L = fj * lj;
#pragma unroll
        for (int o = 8; o > 0; o >>= 1) L += __shfl_xor_sync(0xffffffffu, L, o);
        fj = fj / L;
        float f[4];
#pragma unroll
        for (int k = 0; k < 4; k++) f[k] = __shfl_sync(0xffffffffu, fj, 4 * k + (lane >> 3));
        if (lane < 16) *bs = make_uint2(0u, 0u);

        uint4* bo = (uint4*)&g_box_o[g][r][0][0] + lane;
        float o0, o1, o2, o3;
        for (int it = 0; it < (1 << 20); it++) {
            uint4 w[4];
#pragma unroll
            for (int k = 0; k < 4; k++)
                asm volatile("ld.relaxed.gpu.global.v4.u32 {%0,%1,%2,%3}, [%4];"
                             : "=r"(w[k].x), "=r"(w[k].y), "=r"(w[k].z), "=r"(w[k].w) : "l"(bo + 32 * k) : "memory");
            bool ok = true;
            o0 = o1 = o2 = o3 = 0.f;
#pragma unroll
            for (int k = 0; k < 4; k++) {
                ok = ok && w[k].x != 0u && w[k].y != 0u && w[k].z != 0u && w[k].w != 0u;
                o0 = fmaf(f[k], box_dec(w[k].x), o0);
                o1 = fmaf(f[k], box_dec(w[k].y), o1);
                o2 = fmaf(f[k], box_dec(w[k].z), o2);
                o3 = fmaf(f[k], box_dec(w[k].w), o3);
            }
#pragma unroll
            for (int o = 8; o <= 16; o <<= 1) {
                o0 += __shfl_xor_sync(0xffffffffu, o0, o);
                o1 += __shfl_xor_sync(0xffffffffu, o1, o);
                o2 += __shfl_xor_sync(0xffffffffu, o2, o);
                o3 += __shfl_xor_sync(0xffffffffu, o3, o);
            }
            if (__all_sync(0xffffffffu, ok)) break;
        }
        if (lane < 8) {
            __nv_bfloat162 a = __floats2bfloat162_rn(o0, o1), b = __floats2bfloat162_rn(o2, o3);
            uint2 pk;
            pk.x = *(uint32_t*)&a;
            pk.y = *(uint32_t*)&b;
            *(uint2*)(out + (size_t)g * REP * DH + r * 32 + lane * 4) = pk;
        }
#pragma unroll
        for (int k = 0; k < 4; k++) bo[32 * k] = make_uint4(0u, 0u, 0u, 0u);
        return;
    }

    float* s_p = (float*)(smem + OFF_P);
    float* s_red = (float*)(smem + OFF_RED);
    float* s_qs = (float*)(smem + OFF_QS);
    float* s_cg = (float*)(smem + OFF_CG);
    float* s_wmax = (float*)(smem + OFF_WMAX);
    float* s_wsum = (float*)(smem + OFF_WSUM);
    float* s_wz = (float*)(smem + OFF_WZ);

    float vs[4], vz[4];
#pragma unroll
    for (int i = 0; i < 4; i++) {
        const int t = tid + i * NCT;
        const int tok = (r + (t >> 5) * CPH) * CHUNK_TOK + (t & 31);
        vs[i] = bf2f(v_scales[g * SKV + tok]);
        vz[i] = bf2f(v_zeros[g * SKV + tok]);
    }
    {
        const int kg = warp >> 2, h = warp & 3;
        const float qscale = 0.08838834764831845f * 1.4426950408889634f;
        const uint2 qq = *(const uint2*)(q + (g * REP + h) * DH + lane * 4);
        const uint2 ss = *(const uint2*)(k_scales + (g * NGK + kg) * DH + lane * 4);
        const uint2 zz = *(const uint2*)(k_zeros + (g * NGK + kg) * DH + lane * 4);
        float4 a;
        a.x = __uint_as_float(qq.x << 16) * __uint_as_float(ss.x << 16) * qscale;
        a.y = __uint_as_float(qq.x & 0xffff0000u) * __uint_as_float(ss.x & 0xffff0000u) * qscale;
        a.z = __uint_as_float(qq.y << 16) * __uint_as_float(ss.y << 16) * qscale;
        a.w = __uint_as_float(qq.y & 0xffff0000u) * __uint_as_float(ss.y & 0xffff0000u) * qscale;
        float c = a.x * __uint_as_float(zz.x << 16) + a.y * __uint_as_float(zz.x & 0xffff0000u) +
                  a.z * __uint_as_float(zz.y << 16) + a.w * __uint_as_float(zz.y & 0xffff0000u);
#pragma unroll
        for (int o = 16; o > 0; o >>= 1) c += __shfl_xor_sync(0xffffffffu, c, o);
        *(float4*)(s_qs + warp * DH + lane * 4) = a;
        if (lane == 0) s_cg[warp] = c;
    }
    __syncthreads();

    int st = 0, ph = 0;
    {
        const int myh = (lane >> 1) & 3;
        const bool b2 = lane & 4, b1 = lane & 2;
        const uint32_t xoff = sb + OFF_RING + (warp * 4 + (lane >> 3)) * (DH * 4) + (lane & 7) * 16;
        float mrun = -INFINITY;
#pragma unroll 1
        for (int kg = 0; kg < NGK; kg++) {
            float4 qr[REP][4];
#pragma unroll
            for (int h = 0; h < REP; h++)
#pragma unroll
                for (int j = 0; j < 4; j++)
                    qr[h][j] = *(const float4*)(s_qs + (kg * REP + h) * DH + ((lane & 7) + 8 * j) * 4);
            const float cg = s_cg[kg * REP + myh];
#pragma unroll 1
            for (int c = kg * (NCH / NGK); c < (kg + 1) * (NCH / NGK); c++) {
                mbar_wait(bar_full + st * 8, ph);
                const uint32_t xa = xoff + st * CHUNK_BYTES;
                int4 x[4];
#pragma unroll
                for (int j = 0; j < 4; j++) x[j] = lds_i4(xa + j * 128);
                __syncwarp();
                if (lane == 0) mbar_arrive(bar_empty + st * 8);
                float s[REP] = {0.f, 0.f, 0.f, 0.f};
#pragma unroll
                for (int j = 0; j < 4; j++) {
                    const float f0 = (float)x[j].x, f1 = (float)x[j].y, f2 = (float)x[j].z, f3 = (float)x[j].w;
#pragma unroll
                    for (int h = 0; h < REP; h++) {
                        s[h] = fmaf(qr[h][j].x, f0, s[h]);
                        s[h] = fmaf(qr[h][j].y, f1, s[h]);
                        s[h] = fmaf(qr[h][j].z, f2, s[h]);
                        s[h] = fmaf(qr[h][j].w, f3, s[h]);
                    }
                }
                float k0 = (b2 ? s[2] : s[0]) + __shfl_xor_sync(0xffffffffu, b2 ? s[0] : s[2], 4);
                float k1 = (b2 ? s[3] : s[1]) + __shfl_xor_sync(0xffffffffu, b2 ? s[1] : s[3], 4);
                float t = (b1 ? k1 : k0) + __shfl_xor_sync(0xffffffffu, b1 ? k0 : k1, 2);
                t += __shfl_xor_sync(0xffffffffu, t, 1);
                t -= cg;
                if (!(lane & 1)) s_p[c * (CHUNK_TOK * REP) + warp * 16 + (lane >> 1)] = t;
                mrun = fmaxf(mrun, t);
                if (++st == STAGES) { st = 0; ph ^= 1; }
            }
        }
        mrun = fmaxf(mrun, __shfl_xor_sync(0xffffffffu, mrun, 8));
        mrun = fmaxf(mrun, __shfl_xor_sync(0xffffffffu, mrun, 16));
        if (lane < 8 && !(lane & 1)) s_wmax[warp * REP + myh] = mrun;
    }
    consumer_bar();
    {
        float4 M = *(const float4*)(s_wmax);
#pragma unroll
        for (int w = 1; w < NCW; w++) {
            const float4 m = *(const float4*)(s_wmax + w * REP);
            M.x = fmaxf(M.x, m.x); M.y = fmaxf(M.y, m.y); M.z = fmaxf(M.z, m.z); M.w = fmaxf(M.w, m.w);
        }
        float l[4] = {0.f, 0.f, 0.f, 0.f}, z[4] = {0.f, 0.f, 0.f, 0.f};
#pragma unroll
        for (int i = 0; i < 4; i++) {
            float4* pp = (float4*)(s_p + (tid + i * NCT) * REP);
            float4 p = *pp;
            p.x = ex2(p.x - M.x); p.y = ex2(p.y - M.y); p.z = ex2(p.z - M.z); p.w = ex2(p.w - M.w);
            l[0] += p.x; l[1] += p.y; l[2] += p.z; l[3] += p.w;
            p.x *= vs[i]; p.y *= vs[i]; p.z *= vs[i]; p.w *= vs[i];
            z[0] = fmaf(p.x, vz[i], z[0]); z[1] = fmaf(p.y, vz[i], z[1]);
            z[2] = fmaf(p.z, vz[i], z[2]); z[3] = fmaf(p.w, vz[i], z[3]);
            *pp = p;
        }
#pragma unroll
        for (int o = 16; o > 0; o >>= 1)
#pragma unroll
            for (int h = 0; h < 4; h++) {
                l[h] += __shfl_xor_sync(0xffffffffu, l[h], o);
                z[h] += __shfl_xor_sync(0xffffffffu, z[h], o);
            }
        if (lane == 0) {
            *(float4*)(s_wsum + warp * REP) = make_float4(l[0], l[1], l[2], l[3]);
            *(float4*)(s_wz + warp * REP) = make_float4(z[0], z[1], z[2], z[3]);
        }
        consumer_bar();
        if (tid < CPH) {
            const int h = tid >> 2;
            float ls = 0.f;
#pragma unroll
            for (int w = 0; w < NCW; w++) ls += s_wsum[w * REP + h];
            const float mh = h == 0 ? M.x : h == 1 ? M.y : h == 2 ? M.z : M.w;
            asm volatile("st.relaxed.gpu.global.v2.u32 [%0], {%1,%2};" ::"l"(&g_box_s[g][tid][r]), "r"(box_enc(mh)), "r"(box_enc(ls)) : "memory");
        }
    }
    float zc = 0.f;
#pragma unroll
    for (int w = 0; w < NCW; w++) zc += s_wz[w * REP + (tid >> 6)];

    float acc[REP][4];
#pragma unroll
    for (int h = 0; h < REP; h++)
#pragma unroll
        for (int e = 0; e < 4; e++) acc[h][e] = 0.f;
    {
        const uint32_t xoff = sb + OFF_RING + warp * 4 * (DH * 4) + lane * 16;
        const uint32_t poff = sb + OFF_P + warp * 4 * 16;
#pragma unroll 1
        for (int c = 0; c < NCH; c++) {
            float4 p[4];
#pragma unroll
            for (int j = 0; j < 4; j++) p[j] = lds_f4(poff + c * (CHUNK_TOK * 16) + j * 16);
            mbar_wait(bar_full + st * 8, ph);
            const uint32_t xa = xoff + st * CHUNK_BYTES;
            int4 x[4];
#pragma unroll
            for (int j = 0; j < 4; j++) x[j] = lds_i4(xa + j * (DH * 4));
            __syncwarp();
            if (lane == 0) mbar_arrive(bar_empty + st * 8);
#pragma unroll
            for (int j = 0; j < 4; j++) {
                const float f0 = (float)x[j].x, f1 = (float)x[j].y, f2 = (float)x[j].z, f3 = (float)x[j].w;
                acc[0][0] = fmaf(p[j].x, f0, acc[0][0]); acc[0][1] = fmaf(p[j].x, f1, acc[0][1]);
                acc[0][2] = fmaf(p[j].x, f2, acc[0][2]); acc[0][3] = fmaf(p[j].x, f3, acc[0][3]);
                acc[1][0] = fmaf(p[j].y, f0, acc[1][0]); acc[1][1] = fmaf(p[j].y, f1, acc[1][1]);
                acc[1][2] = fmaf(p[j].y, f2, acc[1][2]); acc[1][3] = fmaf(p[j].y, f3, acc[1][3]);
                acc[2][0] = fmaf(p[j].z, f0, acc[2][0]); acc[2][1] = fmaf(p[j].z, f1, acc[2][1]);
                acc[2][2] = fmaf(p[j].z, f2, acc[2][2]); acc[2][3] = fmaf(p[j].z, f3, acc[2][3]);
                acc[3][0] = fmaf(p[j].w, f0, acc[3][0]); acc[3][1] = fmaf(p[j].w, f1, acc[3][1]);
                acc[3][2] = fmaf(p[j].w, f2, acc[3][2]); acc[3][3] = fmaf(p[j].w, f3, acc[3][3]);
            }
            if (++st == STAGES) { st = 0; ph ^= 1; }
        }
    }
#pragma unroll
    for (int h = 0; h < REP; h++)
        *(float4*)(s_red + warp * (REP * DH) + h * DH + lane * 4) = make_float4(acc[h][0], acc[h][1], acc[h][2], acc[h][3]);
    consumer_bar();
    float2 o = make_float2(-zc, -zc);
#pragma unroll
    for (int w = 0; w < NCW; w++) {
        const float2 v = *(const float2*)(s_red + w * (REP * DH) + tid * 2);
        o.x += v.x;
        o.y += v.y;
    }
    asm volatile("st.relaxed.gpu.global.v2.u32 [%0], {%1,%2};"
                 ::"l"(&g_box_o[g][tid >> 4][r][(tid & 15) * 2]), "r"(box_enc(o.x)), "r"(box_enc(o.y)) : "memory");
}

}

extern "C" void kernel_launch(void* const* d_in, const int* in_sizes, int n_in, void* d_out, int out_size) {
    (void)in_sizes; (void)n_in; (void)out_size;
    static bool configured = false;
    if (!configured) {
        cudaFuncSetAttribute(kvq_decode_kernel, cudaFuncAttributeMaxDynamicSharedMemorySize, SMEM_BYTES);
        configured = true;
    }
    kvq_decode_kernel<<<HKV * CPH, NTHREADS, SMEM_BYTES>>>(
        (const __nv_bfloat16*)d_in[0], (const int*)d_in[1], (const int*)d_in[2], (const __nv_bfloat16*)d_in[3],
        (const __nv_bfloat16*)d_in[4], (const __nv_bfloat16*)d_in[5], (const __nv_bfloat16*)d_in[6],
        (__nv_bfloat16*)d_out);
}
```

```cpp
#include <cuda_runtime.h>
#include <cuda_bf16.h>
#include <stdint.h>

namespace {

constexpr int HKV = 8;
constexpr int REP = 4;
constexpr int SKV = 16384;
constexpr int DH = 128;
constexpr int NGK = 2;
constexpr int NCTA = 128;
constexpr int NG = 2;
constexpr int HPG = HKV / NG;
constexpr int CPG = NCTA / NG;
constexpr int CHUNK_TOK = 32;
constexpr int CHUNK_BYTES = CHUNK_TOK * DH * 4;
constexpr int PIECE_BYTES = CHUNK_BYTES / 4;
constexpr int CPS = SKV / CHUNK_TOK / CPG;
constexpr int NCH = CPS * HPG;
constexpr int TOK_PER_CTA = NCH * CHUNK_TOK;
constexpr int OPR = REP * DH / CPG;
#define STAGES 8
#define LEAD 3
#define TAU 640
#define INFLIGHT 4
#define WARM_POLL 58
#define STATS_START 40
#define SEG_DELAY 6
#define EARLY_WARM 1
#define TAPER 0
#define TAPER_CAP 0
constexpr int NCW = 8;
constexpr int NCT = NCW * 32;
constexpr int NTHREADS = NCT + 64;
static_assert(CPS == NCW && HPG == 4 && OPR == 8, "layout assumptions");

constexpr int OFF_RING = 0;
constexpr int OFF_P = OFF_RING + STAGES * CHUNK_BYTES;
constexpr int OFF_QS = OFF_P + TOK_PER_CTA * REP * 4;
constexpr int OFF_CG = OFF_QS + HPG * NGK * REP * DH * 4;
constexpr int OFF_WMAX = OFF_CG + HPG * NGK * REP * 4;
constexpr int OFF_WSZ = OFF_WMAX + HPG * NCW * REP * 4;
constexpr int OFF_F = OFF_WSZ + NCH * 8 * 4;
constexpr int OFF_BAR = OFF_F + HPG * CPG * 4;
constexpr int NBAR = 2 * STAGES + HPG + 1 + 2 + 4;
constexpr int SMEM_BYTES = OFF_BAR + NBAR * 8;

__device__ __align__(128) uint32_t g_box_o[HKV][CPG][CPG][OPR];
__device__ __align__(128) uint2 g_box_s[HKV][CPG][REP];

__device__ __forceinline__ uint32_t smem_u32(const void* p) { return (uint32_t)__cvta_generic_to_shared(p); }
__device__ __forceinline__ void mbar_init(uint32_t bar, uint32_t cnt) {
    asm volatile("mbarrier.init.shared::cta.b64 [%0], %1;" ::"r"(bar), "r"(cnt) : "memory");
}
__device__ __forceinline__ void mbar_expect_tx(uint32_t bar, uint32_t bytes) {
    asm volatile("mbarrier.arrive.expect_tx.shared::cta.b64 _, [%0], %1;" ::"r"(bar), "r"(bytes) : "memory");
}
__device__ __forceinline__ void mbar_arrive(uint32_t bar) {
    asm volatile("mbarrier.arrive.shared::cta.b64 _, [%0];" ::"r"(bar) : "memory");
}
__device__ __forceinline__ void mbar_wait(uint32_t bar, uint32_t parity) {
    uint32_t ok;
    int it = 0;
    do {
        asm volatile(
            "{\n.reg .pred p;\nmbarrier.try_wait.parity.shared::cta.b64 p, [%1], %2;\nselp.u32 %0, 1, 0, p;\n}"
            : "=r"(ok) : "r"(bar), "r"(parity) : "memory");
    } while (!ok && ++it < (1 << 20));
}
#define WAITMODE 0
__device__ __forceinline__ void mbar_wait_c(uint32_t bar, uint32_t parity) {
    mbar_wait(bar, parity);
}
__device__ __forceinline__ void bulk_load(uint32_t dst, const void* src, uint32_t bytes, uint32_t bar) {
    asm volatile("cp.async.bulk.shared::cluster.global.mbarrier::complete_tx::bytes.L2::cache_hint [%0], [%1], %2, [%3], %4;"
                 ::"r"(dst), "l"(src), "r"(bytes), "r"(bar), "l"(0x12F0000000000000ull) : "memory");
}
__device__ __forceinline__ int4 lds_i4(uint32_t a) {
    int4 v;
    asm volatile("ld.shared.v4.s32 {%0,%1,%2,%3}, [%4];" : "=r"(v.x), "=r"(v.y), "=r"(v.z), "=r"(v.w) : "r"(a) : "memory");
    return v;
}
__device__ __forceinline__ float4 lds_f4(uint32_t a) {
    float4 v;
    asm volatile("ld.shared.v4.f32 {%0,%1,%2,%3}, [%4];" : "=f"(v.x), "=f"(v.y), "=f"(v.z), "=f"(v.w) : "r"(a) : "memory");
    return v;
}
__device__ __forceinline__ void consumer_bar() { asm volatile("bar.sync 1, %0;" ::"n"(NCT) : "memory"); }
__device__ __forceinline__ float ex2(float x) {
    float y;
    asm("ex2.approx.ftz.f32 %0, %1;" : "=f"(y) : "f"(x));
    return y;
}
__device__ __forceinline__ float bf2f(__nv_bfloat16 x) { return __bfloat162float(x); }
__device__ __forceinline__ uint32_t gtime32() {
    uint32_t t;
    asm volatile("mov.u32 %0, %%globaltimer_lo;" : "=r"(t));
    return t;
}

#define TSTAMP(i)

__global__ void __launch_bounds__(NTHREADS, 1)
kvq_decode_kernel(const __nv_bfloat16* __restrict__ q, const int* __restrict__ qk, const int* __restrict__ qv,
                  const __nv_bfloat16* __restrict__ k_scales, const __nv_bfloat16* __restrict__ k_zeros,
                  const __nv_bfloat16* __restrict__ v_scales, const __nv_bfloat16* __restrict__ v_zeros,
                  __nv_bfloat16* __restrict__ out) {
    extern __shared__ __align__(128) unsigned char smem[];
    const uint32_t sb = smem_u32(smem);
    const int grp = blockIdx.x & (NG - 1);
    const int r = blockIdx.x / NG;
    const int head0 = grp * HPG;
    const uint32_t bar_full = sb + OFF_BAR, bar_empty = bar_full + STAGES * 8, bar_go = bar_empty + STAGES * 8;
    const uint32_t bar_sent = bar_go + (HPG + 1) * 8, bar_sread = bar_sent + 8, bar_piece = bar_sread + 8;
    const size_t base = ((size_t)head0 * (SKV / CHUNK_TOK) + r) * CHUNK_BYTES;
    const char* ksrc = (const char*)qk + base;
    uint32_t tnext = 0;

    if (threadIdx.x == 0) {
        TSTAMP(0);
        tnext = gtime32() + TAU;
#pragma unroll
        for (int i = 0; i < LEAD; i++) mbar_init(bar_full + i * 8, 1);
        asm volatile("fence.proxy.async.shared::cta;" ::: "memory");
#pragma unroll
        for (int i = 0; i < LEAD; i++) {
            mbar_expect_tx(bar_full + i * 8, CHUNK_BYTES);
            bulk_load(sb + OFF_RING + i * CHUNK_BYTES, ksrc + (size_t)i * CPG * CHUNK_BYTES, CHUNK_BYTES, bar_full + i * 8);
        }
#pragma unroll
        for (int i = LEAD; i < STAGES; i++) mbar_init(bar_full + i * 8, 1);
#pragma unroll
        for (int i = 0; i < STAGES; i++) mbar_init(bar_empty + i * 8, NCW);
#pragma unroll
        for (int i = 0; i < HPG + 1; i++) mbar_init(bar_go + i * 8, 1);
        mbar_init(bar_sent, NCW);
        mbar_init(bar_sread, 1);
#pragma unroll
        for (int i = 0; i < 4; i++) mbar_init(bar_piece + i * 8, 1);
        asm volatile("fence.proxy.async.shared::cta;" ::: "memory");
    }
    const int lane = threadIdx.x & 31;

    if (threadIdx.x < 32) {
        __syncwarp();
        asm volatile("bar.arrive 2, %0;" ::"n"(NTHREADS) : "memory");
        const char* vsrc = (const char*)qv + base;
        if (lane == 0) {
            int st = LEAD % STAGES, ph = (LEAD / STAGES) & 1;
            for (int i = LEAD; i < 2 * NCH - TAPER; i++) {
                if (i >= INFLIGHT) mbar_wait(bar_full + ((i - INFLIGHT) % STAGES) * 8, ((i - INFLIGHT) / STAGES) & 1);
                if (i >= STAGES) mbar_wait(bar_empty + st * 8, ph ^ 1);
                const char* src = (i < NCH ? ksrc : vsrc) + (size_t)(i & (NCH - 1)) * CPG * CHUNK_BYTES;
                uint32_t now = gtime32();
                while ((int)(now - tnext) < 0) now = gtime32();
                tnext = now + TAU;
                mbar_expect_tx(bar_full + st * 8, CHUNK_BYTES);
                bulk_load(sb + OFF_RING + st * CHUNK_BYTES, src, CHUNK_BYTES, bar_full + st * 8);
                if (i == STATS_START) mbar_arrive(bar_go + HPG * 8);
                if (i == WARM_POLL) mbar_arrive(bar_go + (HPG - 1) * 8);
                if (i >= NCH + CPS + SEG_DELAY && (i - NCH - SEG_DELAY) % CPS == 0)
                    mbar_arrive(bar_go + ((i - NCH - SEG_DELAY) / CPS - 1) * 8);
                if (++st == STAGES) { st = 0; ph ^= 1; }
            }
            TSTAMP(1);
        }
        return;
    }
    if (threadIdx.x < 64) {
        float* s_f = (float*)(smem + OFF_F);
        const int oqh = r * OPR / DH;
        asm volatile("bar.sync 2, %0;" ::"n"(NTHREADS) : "memory");
        mbar_wait(bar_go + HPG * 8, 0);
#pragma unroll 1
        for (int seg = 0; seg < HPG; seg++) {
            uint32_t a0, b0, a1, b1;
            for (int it = 0; it < (1 << 20); it++) {
                asm volatile("ld.relaxed.gpu.global.v2.u32 {%0,%1}, [%2];" : "=r"(a0), "=r"(b0)
                             : "l"(&g_box_s[head0 + seg][lane][oqh]) : "memory");
                asm volatile("ld.relaxed.gpu.global.v2.u32 {%0,%1}, [%2];" : "=r"(a1), "=r"(b1)
                             : "l"(&g_box_s[head0 + seg][lane + 32][oqh]) : "memory");
                if (__all_sync(0xffffffffu, (a0 & b0 & a1 & b1 & 1u) != 0u)) break;
            }
            float M = fmaxf(__uint_as_float(a0), __uint_as_float(a1));
#pragma unroll
            for (int o = 16; o > 0; o >>= 1) M = fmaxf(M, __shfl_xor_sync(0xffffffffu, M, o));
            const float e0 = ex2(__uint_as_float(a0) - M), e1 = ex2(__uint_as_float(a1) - M);
            float L = e0 * __uint_as_float(b0) + e1 * __uint_as_float(b1);
#pragma unroll
            for (int o = 16; o > 0; o >>= 1) L += __shfl_xor_sync(0xffffffffu, L, o);
            s_f[seg * CPG + lane] = e0 / L;
            s_f[seg * CPG + lane + 32] = e1 / L;
        }
        __syncwarp();
        if (lane == 0) mbar_arrive(bar_sread);

        uint4* bo = (uint4*)&g_box_o[head0][r][0][0] + lane;
        __nv_bfloat162* po = (__nv_bfloat162*)(out + head0 * (REP * DH) + r * OPR + (lane & 1) * 4 + (lane >> 4) * 2);
        const bool hi = lane & 16;
        uint4 wl[4];
#pragma unroll
        for (int k = 0; k < 4; k++) wl[k] = make_uint4(0u, 0u, 0u, 0u);
#pragma unroll 1
        for (int seg = 0; seg < HPG; seg++) {
            float f[4];
#pragma unroll
            for (int k = 0; k < 4; k++) f[k] = s_f[seg * CPG + 16 * k + (lane >> 1)];
            uint4 w[4];
            if (seg == HPG - 2) {
                mbar_wait(bar_go + (HPG - 1) * 8, 0);
#pragma unroll
                for (int k = 0; k < 4; k++)
                    asm volatile("ld.relaxed.gpu.global.v4.u32 {%0,%1,%2,%3}, [%4];"
                                 : "=r"(wl[k].x), "=r"(wl[k].y), "=r"(wl[k].z), "=r"(wl[k].w)
                                 : "l"(bo + CPG * CPG * OPR / 4 + 32 * k) : "memory");
            }
#pragma unroll
            for (int k = 0; k < 4; k++) w[k] = seg == HPG - 1 ? wl[k] : make_uint4(0u, 0u, 0u, 0u);
            mbar_wait(seg == HPG - 1 ? bar_sent : bar_go + seg * 8, 0);
            for (int it = 0; it < (1 << 20); it++) {
#pragma unroll
                for (int k = 0; k < 4; k++)
                    asm volatile("{\n.reg .pred p;\nsetp.eq.u32 p, %5, 0;\n@p ld.relaxed.gpu.global.v4.u32 {%0,%1,%2,%3}, [%4];\n}"
                                 : "+r"(w[k].x), "+r"(w[k].y), "+r"(w[k].z), "+r"(w[k].w)
                                 : "l"(bo + 32 * k), "r"(w[k].x & w[k].y & w[k].z & w[k].w & 1u) : "memory");
                uint32_t ok = 1u;
#pragma unroll
                for (int k = 0; k < 4; k++) ok &= w[k].x & w[k].y & w[k].z & w[k].w;
                if (__all_sync(0xffffffffu, ok != 0u)) break;
                if (!EARLY_WARM && it == 0 && seg == HPG - 1) mbar_wait(bar_sent, 0);
            }
            float o0 = f[0] * __uint_as_float(w[0].x), o1 = f[0] * __uint_as_float(w[0].y);
            float o2 = f[0] * __uint_as_float(w[0].z), o3 = f[0] * __uint_as_float(w[0].w);
#pragma unroll
            for (int k = 1; k < 4; k++) {
                o0 = fmaf(f[k], __uint_as_float(w[k].x), o0);
                o1 = fmaf(f[k], __uint_as_float(w[k].y), o1);
                o2 = fmaf(f[k], __uint_as_float(w[k].z), o2);
                o3 = fmaf(f[k], __uint_as_float(w[k].w), o3);
            }
            float a0 = (hi ? o2 : o0) + __shfl_xor_sync(0xffffffffu, hi ? o0 : o2, 16);
            float a1 = (hi ? o3 : o1) + __shfl_xor_sync(0xffffffffu, hi ? o1 : o3, 16);
#pragma unroll
            for (int o = 8; o >= 2; o >>= 1) {
                a0 += __shfl_xor_sync(0xffffffffu, a0, o);
                a1 += __shfl_xor_sync(0xffffffffu, a1, o);
            }
            if ((lane & 14) == 0) *po = __floats2bfloat162_rn(a0, a1);
#pragma unroll
            for (int k = 0; k < 4; k++) bo[32 * k] = make_uint4(0u, 0u, 0u, 0u);
            if (seg == HPG - 2 && lane < HPG * REP) g_box_s[head0 + lane / REP][r][lane % REP] = make_uint2(0u, 0u);
            bo += CPG * CPG * OPR / 4;
            po += REP * DH / 2;
        }
        return;
    }

    const int tid = threadIdx.x - 64;
    const int warp = tid >> 5;
    float* s_p = (float*)(smem + OFF_P);
    float* s_qs = (float*)(smem + OFF_QS);
    float* s_cg = (float*)(smem + OFF_CG);
    float* s_wmax = (float*)(smem + OFF_WMAX);
    float* s_wsz = (float*)(smem + OFF_WSZ);

    {
        const int kg = warp >> 2, h = warp & 3;
        const float qscale = 0.08838834764831845f * 1.4426950408889634f;
        uint2 qq[HPG], ss[HPG], zz[HPG];
#pragma unroll
        for (int seg = 0; seg < HPG; seg++) {
            qq[seg] = *(const uint2*)(q + ((head0 + seg) * REP + h) * DH + lane * 4);
            ss[seg] = *(const uint2*)(k_scales + ((head0 + seg) * NGK + kg) * DH + lane * 4);
            zz[seg] = *(const uint2*)(k_zeros + ((head0 + seg) * NGK + kg) * DH + lane * 4);
        }
#pragma unroll
        for (int seg = 0; seg < HPG; seg++) {
            float4 a;
            a.x = __uint_as_float(qq[seg].x << 16) * __uint_as_float(ss[seg].x << 16) * qscale;
            a.y = __uint_as_float(qq[seg].x & 0xffff0000u) * __uint_as_float(ss[seg].x & 0xffff0000u) * qscale;
            a.z = __uint_as_float(qq[seg].y << 16) * __uint_as_float(ss[seg].y << 16) * qscale;
            a.w = __uint_as_float(qq[seg].y & 0xffff0000u) * __uint_as_float(ss[seg].y & 0xffff0000u) * qscale;
            float c = a.x * __uint_as_float(zz[seg].x << 16) + a.y * __uint_as_float(zz[seg].x & 0xffff0000u) +
                      a.z * __uint_as_float(zz[seg].y << 16) + a.w * __uint_as_float(zz[seg].y & 0xffff0000u);
#pragma unroll
            for (int o = 16; o > 0; o >>= 1) c += __shfl_xor_sync(0xffffffffu, c, o);
            *(float4*)(s_qs + (seg * NCW + warp) * DH + lane * 4) = a;
            if (lane == 0) s_cg[seg * NCW + warp] = c;
        }
    }
    __nv_bfloat16 vsb[HPG], vzb[HPG];
#pragma unroll
    for (int i = 0; i < HPG; i++) {
        const int c = warp + i * NCW;
        const int tok = head0 * SKV + (c * CPG + r) * CHUNK_TOK + lane;
        vsb[i] = v_scales[tok];
        vzb[i] = v_zeros[tok];
    }
    asm volatile("bar.sync 2, %0;" ::"n"(NTHREADS) : "memory");

    int st = 0, ph = 0;
    {
        const int myh = (lane >> 1) & 3;
        const bool b2 = lane & 4, b1 = lane & 2;
        const uint32_t xoff = sb + OFF_RING + (warp * 4 + (lane >> 3)) * (DH * 4) + (lane & 7) * 16;
        float mrun = -INFINITY;
#pragma unroll 1
        for (int sg = 0; sg < HPG * NGK; sg++) {
            float4 qr[REP][4];
#pragma unroll
            for (int h = 0; h < REP; h++)
#pragma unroll
                for (int j = 0; j < 4; j++)
                    qr[h][j] = *(const float4*)(s_qs + (sg * REP + h) * DH + ((lane & 7) + 8 * j) * 4);
            const float cg = s_cg[sg * REP + myh];
#pragma unroll 1
            for (int c = sg * (CPS / NGK); c < (sg + 1) * (CPS / NGK); c++) {
                mbar_wait(bar_full + st * 8, ph);
                const uint32_t xa = xoff + st * CHUNK_BYTES;
                int4 x[4];
#pragma unroll
                for (int j = 0; j < 4; j++) x[j] = lds_i4(xa + j * 128);
                __syncwarp();
                if (lane == 0) mbar_arrive(bar_empty + st * 8);
                float s[REP] = {0.f, 0.f, 0.f, 0.f};
#pragma unroll
                for (int j = 0; j < 4; j++) {
                    const float f0 = (float)x[j].x, f1 = (float)x[j].y, f2 = (float)x[j].z, f3 = (float)x[j].w;
#pragma unroll
                    for (int h = 0; h < REP; h++) {
                        s[h] = fmaf(qr[h][j].x, f0, s[h]);
                        s[h] = fmaf(qr[h][j].y, f1, s[h]);
                        s[h] = fmaf(qr[h][j].z, f2, s[h]);
                        s[h] = fmaf(qr[h][j].w, f3, s[h]);
                    }
                }
                float k0 = (b2 ? s[2] : s[0]) + __shfl_xor_sync(0xffffffffu, b2 ? s[0] : s[2], 4);
                float k1 = (b2 ? s[3] : s[1]) + __shfl_xor_sync(0xffffffffu, b2 ? s[1] : s[3], 4);
                float t = (b1 ? k1 : k0) + __shfl_xor_sync(0xffffffffu, b1 ? k0 : k1, 2);
                t += __shfl_xor_sync(0xffffffffu, t, 1);
                t -= cg;
                if (!(lane & 1)) s_p[c * (CHUNK_TOK * REP) + warp * 16 + (lane >> 1)] = t;
                mrun = fmaxf(mrun, t);
                if (++st == STAGES) { st = 0; ph ^= 1; }
            }
            if (sg & 1) {
                mrun = fmaxf(mrun, __shfl_xor_sync(0xffffffffu, mrun, 8));
                mrun = fmaxf(mrun, __shfl_xor_sync(0xffffffffu, mrun, 16));
                if (lane < 8 && !(lane & 1)) s_wmax[((sg >> 1) * NCW + warp) * REP + myh] = mrun;
                mrun = -INFINITY;
            }
        }
    }
    consumer_bar();
#pragma unroll
    for (int i = 0; i < HPG; i++) {
        float4 M = *(const float4*)(s_wmax + i * NCW * REP);
#pragma unroll
        for (int w = 1; w < NCW; w++) {
            const float4 m = *(const float4*)(s_wmax + (i * NCW + w) * REP);
            M.x = fmaxf(M.x, m.x); M.y = fmaxf(M.y, m.y); M.z = fmaxf(M.z, m.z); M.w = fmaxf(M.w, m.w);
        }
        M.x = __uint_as_float(__float_as_uint(M.x) | 1u); M.y = __uint_as_float(__float_as_uint(M.y) | 1u);
        M.z = __uint_as_float(__float_as_uint(M.z) | 1u); M.w = __uint_as_float(__float_as_uint(M.w) | 1u);
        const float vs = bf2f(vsb[i]), vz = bf2f(vzb[i]);
        float4* pp = (float4*)(s_p + (tid + i * NCT) * REP);
        float4 p = *pp;
        p.x = ex2(p.x - M.x); p.y = ex2(p.y - M.y); p.z = ex2(p.z - M.z); p.w = ex2(p.w - M.w);
        const float4 l = p;
        p.x *= vs; p.y *= vs; p.z *= vs; p.w *= vs;
        const float4 z = make_float4(p.x * vz, p.y * vz, p.z * vz, p.w * vz);
        {
            float4 a = (lane & 4) ? make_float4(p.z, p.w, p.x, p.y) : p;
            *pp = (lane & 2) ? make_float4(a.y, a.x, a.w, a.z) : a;
        }
        const bool b4 = lane & 16, b3 = lane & 8, b2 = lane & 4;
        const float u0 = (b4 ? z.x : l.x) + __shfl_xor_sync(0xffffffffu, b4 ? l.x : z.x, 16);
        const float u1 = (b4 ? z.y : l.y) + __shfl_xor_sync(0xffffffffu, b4 ? l.y : z.y, 16);
        const float u2 = (b4 ? z.z : l.z) + __shfl_xor_sync(0xffffffffu, b4 ? l.z : z.z, 16);
        const float u3 = (b4 ? z.w : l.w) + __shfl_xor_sync(0xffffffffu, b4 ? l.w : z.w, 16);
        const float v0 = (b3 ? u2 : u0) + __shfl_xor_sync(0xffffffffu, b3 ? u0 : u2, 8);
        const float v1 = (b3 ? u3 : u1) + __shfl_xor_sync(0xffffffffu, b3 ? u1 : u3, 8);
        float t = (b2 ? v1 : v0) + __shfl_xor_sync(0xffffffffu, b2 ? v0 : v1, 4);
        t += __shfl_xor_sync(0xffffffffu, t, 2);
        t += __shfl_xor_sync(0xffffffffu, t, 1);
        if (!(lane & 3)) s_wsz[(i * NCW + warp) * 8 + (lane >> 2)] = t;
    }
    consumer_bar();
    if (tid < HPG * REP) {
        const int seg = tid / REP, h = tid % REP;
        float ls = 0.f, mh = -INFINITY;
#pragma unroll
        for (int c = 0; c < CPS; c++) {
            ls += s_wsz[(seg * CPS + c) * 8 + h];
            mh = fmaxf(mh, s_wmax[(seg * NCW + c) * REP + h]);
        }
        asm volatile("st.relaxed.gpu.global.v2.u32 [%0], {%1,%2};" ::"l"(&g_box_s[head0 + seg][r][h]),
                     "r"(__float_as_uint(mh) | 1u), "r"(__float_as_uint(ls) | 1u) : "memory");
    }

    const int oh = lane >> 3;
    const int oidx = oh * DH + warp * 16 + (lane & 3) * 4 + ((lane >> 2) & 1) * 2;
    uint32_t* obox = &g_box_o[head0][oidx / OPR][r][oidx % OPR];
    const uint32_t xoff = sb + OFF_RING + (lane >> 2) * (DH * 4) + warp * 64 + (lane & 3) * 16;
    uint32_t pa = sb + OFF_P + (lane >> 2) * 16;
    const bool b2 = lane & 4;
#pragma unroll 1
    for (int seg = 0; seg < HPG; seg++) {
        float zc = 0.f;
#pragma unroll
        for (int c = 0; c < CPS; c++) zc -= s_wsz[(seg * CPS + c) * 8 + 4 + oh];
        if (b2) zc = 0.f;
        float acc[REP][4];
#pragma unroll
        for (int e = 0; e < 4; e++) {
            acc[0][e] = zc;
            acc[1][e] = acc[2][e] = acc[3][e] = 0.f;
        }
        if (seg == HPG - 2) mbar_wait(bar_sread, 0);
#pragma unroll 1
        for (int c = 0; c < CPS; c++) {
            float4 p[4];
#pragma unroll
            for (int j = 0; j < 4; j++) p[j] = lds_f4(pa + j * 128);
            pa += CHUNK_TOK * 16;
            const uint32_t xa = xoff + st * CHUNK_BYTES;
            mbar_wait_c(bar_full + st * 8, ph);
            int4 x[4];
#pragma unroll
            for (int j = 0; j < 4; j++) x[j] = lds_i4(xa + j * PIECE_BYTES);
            __syncwarp();
            if (lane == 0) mbar_arrive(bar_empty + st * 8);
#pragma unroll
            for (int j = 0; j < 4; j++) {
                const float f0 = (float)x[j].x, f1 = (float)x[j].y, f2 = (float)x[j].z, f3 = (float)x[j].w;
                acc[0][0] = fmaf(p[j].x, f0, acc[0][0]); acc[0][1] = fmaf(p[j].x, f1, acc[0][1]);
                acc[0][2] = fmaf(p[j].x, f2, acc[0][2]); acc[0][3] = fmaf(p[j].x, f3, acc[0][3]);
                acc[1][0] = fmaf(p[j].y, f0, acc[1][0]); acc[1][1] = fmaf(p[j].y, f1, acc[1][1]);
                acc[1][2] = fmaf(p[j].y, f2, acc[1][2]); acc[1][3] = fmaf(p[j].y, f3, acc[1][3]);
                acc[2][0] = fmaf(p[j].z, f0, acc[2][0]); acc[2][1] = fmaf(p[j].z, f1, acc[2][1]);
                acc[2][2] = fmaf(p[j].z, f2, acc[2][2]); acc[2][3] = fmaf(p[j].z, f3, acc[2][3]);
                acc[3][0] = fmaf(p[j].w, f0, acc[3][0]); acc[3][1] = fmaf(p[j].w, f1, acc[3][1]);
                acc[3][2] = fmaf(p[j].w, f2, acc[3][2]); acc[3][3] = fmaf(p[j].w, f3, acc[3][3]);
            }
            if (++st == STAGES) { st = 0; ph ^= 1; }
        }
        float u[2][4], v[4];
#pragma unroll
        for (int h = 0; h < 2; h++)
#pragma unroll
            for (int e = 0; e < 4; e++) u[h][e] = acc[h][e] + __shfl_xor_sync(0xffffffffu, acc[h + 2][e], 16);
#pragma unroll
        for (int e = 0; e < 4; e++) v[e] = u[0][e] + __shfl_xor_sync(0xffffffffu, u[1][e], 8);
        const float ox = (b2 ? v[2] : v[0]) + __shfl_xor_sync(0xffffffffu, b2 ? v[0] : v[2], 4);
        const float oy = (b2 ? v[3] : v[1]) + __shfl_xor_sync(0xffffffffu, b2 ? v[1] : v[3], 4);
        asm volatile("st.relaxed.gpu.global.v2.u32 [%0], {%1,%2};"
                     ::"l"(obox), "r"(__float_as_uint(ox) | 1u), "r"(__float_as_uint(oy) | 1u) : "memory");
        obox += CPG * CPG * OPR;
    }
    if (lane == 0) mbar_arrive(bar_sent);
}

}

extern "C" void kernel_launch(void* const* d_in, const int* in_sizes, int n_in, void* d_out, int out_size) {
    (void)in_sizes; (void)n_in; (void)out_size;
    static bool configured = false;
    if (!configured) {
        cudaFuncSetAttribute(kvq_decode_kernel, cudaFuncAttributeMaxDynamicSharedMemorySize, SMEM_BYTES);
        configured = true;
    }
    kvq_decode_kernel<<<NCTA, NTHREADS, SMEM_BYTES>>>(
        (const __nv_bfloat16*)d_in[0], (const int*)d_in[1], (const int*)d_in[2], (const __nv_bfloat16*)d_in[3],
        (const __nv_bfloat16*)d_in[4], (const __nv_bfloat16*)d_in[5], (const __nv_bfloat16*)d_in[6],
        (__nv_bfloat16*)d_out);
}
```

```cpp
#include <cuda_runtime.h>
#include <cuda_bf16.h>
#include <stdint.h>

namespace {

constexpr int HKV = 8;
constexpr int REP = 4;
constexpr int SKV = 16384;
constexpr int DH = 128;
constexpr int NGK = 2;
constexpr int NCTA = 128;
constexpr int NG = 2;
constexpr int HPG = HKV / NG;
constexpr int CPG = NCTA / NG;
constexpr int CHUNK_TOK = 32;
constexpr int CHUNK_BYTES = CHUNK_TOK * DH * 4;
constexpr int CPS = SKV / CHUNK_TOK / CPG;
constexpr int NCH = CPS * HPG;
constexpr int TOK_PER_CTA = NCH * CHUNK_TOK;
constexpr int OPR = REP * DH / CPG;
constexpr int STAGES = 8;
constexpr int LEAD = 2;
constexpr int INFLIGHT = 4;
constexpr int STATS_START = 40;
constexpr int SEG_DELAY = 6;
constexpr double TAU_EFF = 0.976;
constexpr int NCW = 8;
constexpr int NCT = NCW * 32;
constexpr int NTHREADS = NCT + 64;
static_assert(CPS == NCW && HPG == 4 && OPR == 8, "layout assumptions");

constexpr int OFF_RING = 0;
constexpr int OFF_P = OFF_RING + STAGES * CHUNK_BYTES;
constexpr int OFF_QS = OFF_P + TOK_PER_CTA * REP * 4;
constexpr int OFF_CG = OFF_QS + HPG * NGK * REP * DH * 4;
constexpr int OFF_WMAX = OFF_CG + HPG * NGK * REP * 4;
constexpr int OFF_WSZ = OFF_WMAX + HPG * NCW * REP * 4;
constexpr int OFF_F = OFF_WSZ + NCH * 8 * 4;
constexpr int OFF_MISC = OFF_F + HPG * CPG * 4;
constexpr int OFF_BAR = OFF_MISC + 16;
constexpr int NBAR = 2 * STAGES + HPG + 3;
constexpr int SMEM_BYTES = OFF_BAR + NBAR * 8;

__device__ __align__(128) uint32_t g_box_o[NG][3][CPG][CPG][OPR];
__device__ __align__(128) uint2 g_box_s[HKV][CPG][REP];
__device__ uint32_t g_epoch[NCTA];
constexpr int SET_WORDS = CPG * CPG * OPR;

__device__ __forceinline__ uint32_t smem_u32(const void* p) { return (uint32_t)__cvta_generic_to_shared(p); }
__device__ __forceinline__ void mbar_init(uint32_t bar, uint32_t cnt) {
    asm volatile("mbarrier.init.shared::cta.b64 [%0], %1;" ::"r"(bar), "r"(cnt) : "memory");
}
__device__ __forceinline__ void mbar_expect_tx(uint32_t bar, uint32_t bytes) {
    asm volatile("mbarrier.arrive.expect_tx.shared::cta.b64 _, [%0], %1;" ::"r"(bar), "r"(bytes) : "memory");
}
__device__ __forceinline__ void mbar_arrive(uint32_t bar) {
    asm volatile("mbarrier.arrive.shared::cta.b64 _, [%0];" ::"r"(bar) : "memory");
}
__device__ __forceinline__ void mbar_wait(uint32_t bar, uint32_t parity) {
    uint32_t ok;
    int it = 0;
    do {
        asm volatile(
            "{\n.reg .pred p;\nmbarrier.try_wait.parity.shared::cta.b64 p, [%1], %2;\nselp.u32 %0, 1, 0, p;\n}"
            : "=r"(ok) : "r"(bar), "r"(parity) : "memory");
    } while (!ok && ++it < (1 << 20));
}
__device__ __forceinline__ void bulk_load(uint32_t dst, const void* src, uint32_t bytes, uint32_t bar) {
    asm volatile("{\n.reg .b64 pol;\ncreatepolicy.fractional.L2::evict_first.b64 pol, 1.0;\n"
                 "cp.async.bulk.shared::cluster.global.mbarrier::complete_tx::bytes.L2::cache_hint [%0], [%1], %2, [%3], pol;\n}"
                 ::"r"(dst), "l"(src), "r"(bytes), "r"(bar) : "memory");
}
__device__ __forceinline__ int4 lds_i4(uint32_t a) {
    int4 v;
    asm volatile("ld.shared.v4.s32 {%0,%1,%2,%3}, [%4];" : "=r"(v.x), "=r"(v.y), "=r"(v.z), "=r"(v.w) : "r"(a) : "memory");
    return v;
}
__device__ __forceinline__ float4 lds_f4(uint32_t a) {
    float4 v;
    asm volatile("ld.shared.v4.f32 {%0,%1,%2,%3}, [%4];" : "=f"(v.x), "=f"(v.y), "=f"(v.z), "=f"(v.w) : "r"(a) : "memory");
    return v;
}
__device__ __forceinline__ void consumer_bar() { asm volatile("bar.sync 1, %0;" ::"n"(NCT) : "memory"); }
__device__ __forceinline__ float ex2(float x) {
    float y;
    asm("ex2.approx.ftz.f32 %0, %1;" : "=f"(y) : "f"(x));
    return y;
}
__device__ __forceinline__ float bf2f(__nv_bfloat16 x) { return __bfloat162float(x); }
__device__ __forceinline__ uint32_t gtime32() {
    uint32_t t;
    asm volatile("mov.u32 %0, %%globaltimer_lo;" : "=r"(t));
    return t;
}
__device__ __forceinline__ uint32_t tagged(float v, uint32_t tag) { return (__float_as_uint(v) & ~3u) | tag; }
__device__ __forceinline__ float untag(uint32_t w) { return __uint_as_float(w & ~3u); }
__device__ __forceinline__ uint32_t mism4(const uint4& w, uint32_t tag) {
    return ((w.x ^ tag) | (w.y ^ tag)) | ((w.z ^ tag) | (w.w ^ tag));
}

__global__ void __launch_bounds__(NTHREADS, 1)
kvq_decode_kernel(const __nv_bfloat16* __restrict__ q, const int* __restrict__ qk, const int* __restrict__ qv,
                  const __nv_bfloat16* __restrict__ k_scales, const __nv_bfloat16* __restrict__ k_zeros,
                  const __nv_bfloat16* __restrict__ v_scales, const __nv_bfloat16* __restrict__ v_zeros,
                  __nv_bfloat16* __restrict__ out, int tau) {
    extern __shared__ __align__(128) unsigned char smem[];
    const uint32_t sb = smem_u32(smem);
    const int grp = blockIdx.x & (NG - 1);
    const int r = blockIdx.x / NG;
    const int head0 = grp * HPG;
    const uint32_t bar_full = sb + OFF_BAR, bar_empty = bar_full + STAGES * 8, bar_go = bar_empty + STAGES * 8;
    const uint32_t bar_sent = bar_go + HPG * 8, bar_mdone = bar_sent + 8;
    const size_t base = ((size_t)head0 * (SKV / CHUNK_TOK) + r) * CHUNK_BYTES;
    const char* ksrc = (const char*)qk + base;
    uint32_t tnext = 0;

    if (threadIdx.x == 0) {
        tnext = gtime32() + tau;
#pragma unroll
        for (int i = 0; i < LEAD; i++) mbar_init(bar_full + i * 8, 1);
        asm volatile("fence.proxy.async.shared::cta;" ::: "memory");
#pragma unroll
        for (int i = 0; i < LEAD; i++) {
            mbar_expect_tx(bar_full + i * 8, CHUNK_BYTES);
            bulk_load(sb + OFF_RING + i * CHUNK_BYTES, ksrc + (size_t)i * CPG * CHUNK_BYTES, CHUNK_BYTES, bar_full + i * 8);
        }
#pragma unroll
        for (int i = LEAD; i < STAGES; i++) mbar_init(bar_full + i * 8, 1);
#pragma unroll
        for (int i = 0; i < STAGES; i++) mbar_init(bar_empty + i * 8, NCW);
#pragma unroll
        for (int i = 0; i < HPG; i++) mbar_init(bar_go + i * 8, 1);
        mbar_init(bar_sent, NCW);
        mbar_init(bar_mdone, 1);
        mbar_init(bar_mdone + 8, 1);
        asm volatile("fence.proxy.async.shared::cta;" ::: "memory");
    }
    const int lane = threadIdx.x & 31;
    volatile uint32_t* s_misc = (volatile uint32_t*)(smem + OFF_MISC);

    if (threadIdx.x < 32) {
        __syncwarp();
        asm volatile("bar.arrive 2, %0;" ::"n"(NTHREADS) : "memory");
        if (lane == 0) {
            const char* vsrc = (const char*)qv + base;
            uint32_t t1 = gtime32(), t2 = t1;
            for (int it = 0; it < 4096 && t2 == t1; it++) t2 = gtime32();
            t1 = t2;
            for (int it = 0; it < 4096 && t2 == t1; it++) t2 = gtime32();
            const int tick = (int)(t2 - t1);
            if (tick == 0) tau = 0;
            int st = LEAD % STAGES, ph = (LEAD / STAGES) & 1;
            for (int i = LEAD; i < 2 * NCH; i++) {
                if (i >= INFLIGHT) mbar_wait(bar_full + ((i - INFLIGHT) % STAGES) * 8, ((i - INFLIGHT) / STAGES) & 1);
                if (i >= STAGES) mbar_wait(bar_empty + st * 8, ph ^ 1);
                const char* src = (i < NCH ? ksrc : vsrc) + (size_t)(i & (NCH - 1)) * CPG * CHUNK_BYTES;
                if (tau > 0) {
                    uint32_t now = gtime32();
                    for (int it = 0; it < (1 << 16) && (int)(now - tnext) < 0; it++) now = gtime32();
                    if ((int)(now - tnext) > tick) tnext = now - tick;
                    tnext += tau;
                }
                mbar_expect_tx(bar_full + st * 8, CHUNK_BYTES);
                bulk_load(sb + OFF_RING + st * CHUNK_BYTES, src, CHUNK_BYTES, bar_full + st * 8);
                if (i == STATS_START) mbar_arrive(bar_go + (HPG - 1) * 8);
                if (i >= NCH + CPS + SEG_DELAY && (i - NCH - SEG_DELAY) % CPS == 0)
                    mbar_arrive(bar_go + ((i - NCH - SEG_DELAY) / CPS - 1) * 8);
                if (++st == STAGES) { st = 0; ph ^= 1; }
            }
        }
        return;
    }
    if (threadIdx.x < 64) {
        float* s_f = (float*)(smem + OFF_F);
        if (lane == 0) {
            const uint32_t e = g_epoch[blockIdx.x] + 1u;
            g_epoch[blockIdx.x] = e;
            s_misc[0] = e & 1u;
        }
        asm volatile("bar.sync 2, %0;" ::"n"(NTHREADS) : "memory");
        const uint32_t par = s_misc[0];
        const int oqh = r * OPR / DH;
        mbar_wait(bar_go + (HPG - 1) * 8, 0);
#pragma unroll 1
        for (int seg = 0; seg < HPG; seg++) {
            uint4 a;
            for (int it = 0; it < (1 << 20); it++) {
                asm volatile("ld.relaxed.gpu.global.v2.u32 {%0,%1}, [%2];" : "=r"(a.x), "=r"(a.y)
                             : "l"(&g_box_s[head0 + seg][lane][oqh]) : "memory");
                asm volatile("ld.relaxed.gpu.global.v2.u32 {%0,%1}, [%2];" : "=r"(a.z), "=r"(a.w)
                             : "l"(&g_box_s[head0 + seg][lane + 32][oqh]) : "memory");
                if (__all_sync(0xffffffffu, (mism4(a, par) & 3u) == 0u)) break;
            }
            float M = fmaxf(untag(a.x), untag(a.z));
#pragma unroll
            for (int o = 16; o > 0; o >>= 1) M = fmaxf(M, __shfl_xor_sync(0xffffffffu, M, o));
            const float e0 = ex2(untag(a.x) - M), e1 = ex2(untag(a.z) - M);
            float L = e0 * untag(a.y) + e1 * untag(a.w);
#pragma unroll
            for (int o = 16; o > 0; o >>= 1) L += __shfl_xor_sync(0xffffffffu, L, o);
            s_f[seg * CPG + lane] = e0 / L;
            s_f[seg * CPG + lane + 32] = e1 / L;
        }
        __syncwarp();
        const uint4* box = (const uint4*)&g_box_o[grp][0][r][0][0] + lane;
        const bool hi = lane & 16;
#pragma unroll 1
        for (int seg = 0; seg < HPG; seg++) {
            const bool last = seg == HPG - 1;
            const uint4* bo = box + (last ? 0 : seg) * (SET_WORDS / 4);
            const uint32_t tag = par | (last ? 2u : 0u);
            __nv_bfloat162* po = (__nv_bfloat162*)(out + (head0 + seg) * (REP * DH) + r * OPR + (lane & 1) * 4 + (lane >> 4) * 2);
            float f[4];
#pragma unroll
            for (int k = 0; k < 4; k++) f[k] = s_f[seg * CPG + 16 * k + (lane >> 1)];
            uint4 w[4];
#pragma unroll
            for (int k = 0; k < 4; k++) w[k] = make_uint4(0u, 0u, 0u, 0u);
            uint32_t miss[4] = {1u, 1u, 1u, 1u};
            mbar_wait(last ? bar_sent : bar_go + seg * 8, 0);
            for (int it = 0; it < (1 << 20); it++) {
#pragma unroll
                for (int k = 0; k < 4; k++)
                    asm volatile("{\n.reg .pred p;\nsetp.ne.u32 p, %5, 0;\n@p ld.relaxed.gpu.global.v4.u32 {%0,%1,%2,%3}, [%4];\n}"
                                 : "+r"(w[k].x), "+r"(w[k].y), "+r"(w[k].z), "+r"(w[k].w)
                                 : "l"(bo + 32 * k), "r"(miss[k]) : "memory");
#pragma unroll
                for (int k = 0; k < 4; k++) miss[k] = mism4(w[k], tag) & 3u;
                if (__all_sync(0xffffffffu, (miss[0] | miss[1] | miss[2] | miss[3]) == 0u)) break;
            }
            float o0 = f[0] * untag(w[0].x), o1 = f[0] * untag(w[0].y);
            float o2 = f[0] * untag(w[0].z), o3 = f[0] * untag(w[0].w);
#pragma unroll
            for (int k = 1; k < 4; k++) {
                o0 = fmaf(f[k], untag(w[k].x), o0);
                o1 = fmaf(f[k], untag(w[k].y), o1);
                o2 = fmaf(f[k], untag(w[k].z), o2);
                o3 = fmaf(f[k], untag(w[k].w), o3);
            }
            float a0 = (hi ? o2 : o0) + __shfl_xor_sync(0xffffffffu, hi ? o0 : o2, 16);
            float a1 = (hi ? o3 : o1) + __shfl_xor_sync(0xffffffffu, hi ? o1 : o3, 16);
#pragma unroll
            for (int o = 8; o >= 2; o >>= 1) {
                a0 += __shfl_xor_sync(0xffffffffu, a0, o);
                a1 += __shfl_xor_sync(0xffffffffu, a1, o);
            }
            if ((lane & 14) == 0) *po = __floats2bfloat162_rn(a0, a1);
            if (seg < 2 && lane == 0) mbar_arrive(bar_mdone + seg * 8);
        }
        return;
    }

    const int tid = threadIdx.x - 64;
    const int warp = tid >> 5;
    float* s_p = (float*)(smem + OFF_P);
    float* s_qs = (float*)(smem + OFF_QS);
    float* s_cg = (float*)(smem + OFF_CG);
    float* s_wmax = (float*)(smem + OFF_WMAX);
    float* s_wsz = (float*)(smem + OFF_WSZ);

    {
        const int kg = warp >> 2, h = warp & 3;
        const float qscale = 0.08838834764831845f * 1.4426950408889634f;
        uint2 qq[HPG], ss[HPG], zz[HPG];
#pragma unroll
        for (int seg = 0; seg < HPG; seg++) {
            qq[seg] = *(const uint2*)(q + ((head0 + seg) * REP + h) * DH + lane * 4);
            ss[seg] = *(const uint2*)(k_scales + ((head0 + seg) * NGK + kg) * DH + lane * 4);
            zz[seg] = *(const uint2*)(k_zeros + ((head0 + seg) * NGK + kg) * DH + lane * 4);
        }
#pragma unroll
        for (int seg = 0; seg < HPG; seg++) {
            float4 a;
            a.x = __uint_as_float(qq[seg].x << 16) * __uint_as_float(ss[seg].x << 16) * qscale;
            a.y = __uint_as_float(qq[seg].x & 0xffff0000u) * __uint_as_float(ss[seg].x & 0xffff0000u) * qscale;
            a.z = __uint_as_float(qq[seg].y << 16) * __uint_as_float(ss[seg].y << 16) * qscale;
            a.w = __uint_as_float(qq[seg].y & 0xffff0000u) * __uint_as_float(ss[seg].y & 0xffff0000u) * qscale;
            float c = a.x * __uint_as_float(zz[seg].x << 16) + a.y * __uint_as_float(zz[seg].x & 0xffff0000u) +
                      a.z * __uint_as_float(zz[seg].y << 16) + a.w * __uint_as_float(zz[seg].y & 0xffff0000u);
#pragma unroll
            for (int o = 16; o > 0; o >>= 1) c += __shfl_xor_sync(0xffffffffu, c, o);
            *(float4*)(s_qs + (seg * NCW + warp) * DH + lane * 4) = a;
            if (lane == 0) s_cg[seg * NCW + warp] = c;
        }
    }
    __nv_bfloat16 vsb[HPG], vzb[HPG];
#pragma unroll
    for (int i = 0; i < HPG; i++) {
        const int c = warp + i * NCW;
        const int tok = head0 * SKV + (c * CPG + r) * CHUNK_TOK + lane;
        vsb[i] = v_scales[tok];
        vzb[i] = v_zeros[tok];
    }
    asm volatile("bar.sync 2, %0;" ::"n"(NTHREADS) : "memory");

    int st = 0, ph = 0;
    {
        const int myh = (lane >> 1) & 3;
        const bool b2 = lane & 4, b1 = lane & 2;
        const uint32_t xoff = sb + OFF_RING + (warp * 4 + (lane >> 3)) * (DH * 4) + (lane & 7) * 16;
        float mrun = -INFINITY;
#pragma unroll 1
        for (int sg = 0; sg < HPG * NGK; sg++) {
            float4 qr[REP][4];
#pragma unroll
            for (int h = 0; h < REP; h++)
#pragma unroll
                for (int j = 0; j < 4; j++)
                    qr[h][j] = *(const float4*)(s_qs + (sg * REP + h) * DH + ((lane & 7) + 8 * j) * 4);
            const float cg = s_cg[sg * REP + myh];
#pragma unroll 1
            for (int c = sg * (CPS / NGK); c < (sg + 1) * (CPS / NGK); c++) {
                mbar_wait(bar_full + st * 8, ph);
                const uint32_t xa = xoff + st * CHUNK_BYTES;
                int4 x[4];
#pragma unroll
                for (int j = 0; j < 4; j++) x[j] = lds_i4(xa + j * 128);
                __syncwarp();
                if (lane == 0) mbar_arrive(bar_empty + st * 8);
                float s[REP] = {0.f, 0.f, 0.f, 0.f};
#pragma unroll
                for (int j = 0; j < 4; j++) {
                    const float f0 = (float)x[j].x, f1 = (float)x[j].y, f2 = (float)x[j].z, f3 = (float)x[j].w;
#pragma unroll
                    for (int h = 0; h < REP; h++) {
                        s[h] = fmaf(qr[h][j].x, f0, s[h]);
                        s[h] = fmaf(qr[h][j].y, f1, s[h]);
                        s[h] = fmaf(qr[h][j].z, f2, s[h]);
                        s[h] = fmaf(qr[h][j].w, f3, s[h]);
                    }
                }
                float k0 = (b2 ? s[2] : s[0]) + __shfl_xor_sync(0xffffffffu, b2 ? s[0] : s[2], 4);
                float k1 = (b2 ? s[3] : s[1]) + __shfl_xor_sync(0xffffffffu, b2 ? s[1] : s[3], 4);
                float t = (b1 ? k1 : k0) + __shfl_xor_sync(0xffffffffu, b1 ? k0 : k1, 2);
                t += __shfl_xor_sync(0xffffffffu, t, 1);
                t -= cg;
                if (!(lane & 1)) s_p[c * (CHUNK_TOK * REP) + warp * 16 + (lane >> 1)] = t;
                mrun = fmaxf(mrun, t);
                if (++st == STAGES) { st = 0; ph ^= 1; }
            }
            if (sg & 1) {
                mrun = fmaxf(mrun, __shfl_xor_sync(0xffffffffu, mrun, 8));
                mrun = fmaxf(mrun, __shfl_xor_sync(0xffffffffu, mrun, 16));
                if (lane < 8 && !(lane & 1)) s_wmax[((sg >> 1) * NCW + warp) * REP + myh] = mrun;
                mrun = -INFINITY;
            }
        }
    }
    const uint32_t par = s_misc[0];
    consumer_bar();
#pragma unroll
    for (int i = 0; i < HPG; i++) {
        float4 M = *(const float4*)(s_wmax + i * NCW * REP);
#pragma unroll
        for (int w = 1; w < NCW; w++) {
            const float4 m = *(const float4*)(s_wmax + (i * NCW + w) * REP);
            M.x = fmaxf(M.x, m.x); M.y = fmaxf(M.y, m.y); M.z = fmaxf(M.z, m.z); M.w = fmaxf(M.w, m.w);
        }
        M.x = untag(__float_as_uint(M.x)); M.y = untag(__float_as_uint(M.y));
        M.z = untag(__float_as_uint(M.z)); M.w = untag(__float_as_uint(M.w));
        const float vs = bf2f(vsb[i]), vz = bf2f(vzb[i]);
        float4* pp = (float4*)(s_p + (tid + i * NCT) * REP);
        float4 p = *pp;
        p.x = ex2(p.x - M.x); p.y = ex2(p.y - M.y); p.z = ex2(p.z - M.z); p.w = ex2(p.w - M.w);
        const float4 l = p;
        p.x *= vs; p.y *= vs; p.z *= vs; p.w *= vs;
        const float4 z = make_float4(p.x * vz, p.y * vz, p.z * vz, p.w * vz);
        {
            float4 a = (lane & 4) ? make_float4(p.z, p.w, p.x, p.y) : p;
            *pp = (lane & 2) ? make_float4(a.y, a.x, a.w, a.z) : a;
        }
        const bool b4 = lane & 16, b3 = lane & 8, b2 = lane & 4;
        const float u0 = (b4 ? z.x : l.x) + __shfl_xor_sync(0xffffffffu, b4 ? l.x : z.x, 16);
        const float u1 = (b4 ? z.y : l.y) + __shfl_xor_sync(0xffffffffu, b4 ? l.y : z.y, 16);
        const float u2 = (b4 ? z.z : l.z) + __shfl_xor_sync(0xffffffffu, b4 ? l.z : z.z, 16);
        const float u3 = (b4 ? z.w : l.w) + __shfl_xor_sync(0xffffffffu, b4 ? l.w : z.w, 16);
        const float v0 = (b3 ? u2 : u0) + __shfl_xor_sync(0xffffffffu, b3 ? u0 : u2, 8);
        const float v1 = (b3 ? u3 : u1) + __shfl_xor_sync(0xffffffffu, b3 ? u1 : u3, 8);
        float t = (b2 ? v1 : v0) + __shfl_xor_sync(0xffffffffu, b2 ? v0 : v1, 4);
        t += __shfl_xor_sync(0xffffffffu, t, 2);
        t += __shfl_xor_sync(0xffffffffu, t, 1);
        if (!(lane & 3)) s_wsz[(i * NCW + warp) * 8 + (lane >> 2)] = t;
    }
    consumer_bar();
    if (tid < HPG * REP) {
        const int seg = tid / REP, h = tid % REP;
        float ls = 0.f, mh = -INFINITY;
#pragma unroll
        for (int c = 0; c < CPS; c++) {
            ls += s_wsz[(seg * CPS + c) * 8 + h];
            mh = fmaxf(mh, s_wmax[(seg * NCW + c) * REP + h]);
        }
        asm volatile("st.relaxed.gpu.global.v2.u32 [%0], {%1,%2};" ::"l"(&g_box_s[head0 + seg][r][h]),
                     "r"(tagged(mh, par)), "r"(tagged(ls, par)) : "memory");
    }

    const int oh = lane >> 3;
    const int oidx = oh * DH + warp * 16 + (lane & 3) * 4 + ((lane >> 2) & 1) * 2;
    uint32_t* obox = &g_box_o[grp][0][oidx / OPR][r][oidx % OPR];
    const uint32_t xoff = sb + OFF_RING + (lane >> 2) * (DH * 4) + warp * 64 + (lane & 3) * 16;
    uint32_t pa = sb + OFF_P + (lane >> 2) * 16;
    const bool b2 = lane & 4;
#pragma unroll 1
    for (int seg = 0; seg < HPG; seg++) {
        float zc = 0.f;
#pragma unroll
        for (int c = 0; c < CPS; c++) zc -= s_wsz[(seg * CPS + c) * 8 + 4 + oh];
        if (b2) zc = 0.f;
        float acc[REP][4];
#pragma unroll
        for (int e = 0; e < 4; e++) {
            acc[0][e] = zc;
            acc[1][e] = acc[2][e] = acc[3][e] = 0.f;
        }
        uint32_t* ob = obox + (seg == HPG - 1 ? 0 : seg) * SET_WORDS;
        const uint32_t tag = par | (seg == HPG - 1 ? 2u : 0u);
        if (seg == HPG - 1) mbar_wait(bar_mdone + 8, 0);
#pragma unroll 1
        for (int c = 0; c < CPS; c++) {
            float4 p[4];
#pragma unroll
            for (int j = 0; j < 4; j++) p[j] = lds_f4(pa + j * 128);
            pa += CHUNK_TOK * 16;
            const uint32_t xa = xoff + st * CHUNK_BYTES;
            mbar_wait(bar_full + st * 8, ph);
            int4 x[4];
#pragma unroll
            for (int j = 0; j < 4; j++) x[j] = lds_i4(xa + j * (8 * DH * 4));
            __syncwarp();
            if (lane == 0) mbar_arrive(bar_empty + st * 8);
#pragma unroll
            for (int j = 0; j < 4; j++) {
                const float f0 = (float)x[j].x, f1 = (float)x[j].y, f2 = (float)x[j].z, f3 = (float)x[j].w;
                acc[0][0] = fmaf(p[j].x, f0, acc[0][0]); acc[0][1] = fmaf(p[j].x, f1, acc[0][1]);
                acc[0][2] = fmaf(p[j].x, f2, acc[0][2]); acc[0][3] = fmaf(p[j].x, f3, acc[0][3]);
                acc[1][0] = fmaf(p[j].y, f0, acc[1][0]); acc[1][1] = fmaf(p[j].y, f1, acc[1][1]);
                acc[1][2] = fmaf(p[j].y, f2, acc[1][2]); acc[1][3] = fmaf(p[j].y, f3, acc[1][3]);
                acc[2][0] = fmaf(p[j].z, f0, acc[2][0]); acc[2][1] = fmaf(p[j].z, f1, acc[2][1]);
                acc[2][2] = fmaf(p[j].z, f2, acc[2][2]); acc[2][3] = fmaf(p[j].z, f3, acc[2][3]);
                acc[3][0] = fmaf(p[j].w, f0, acc[3][0]); acc[3][1] = fmaf(p[j].w, f1, acc[3][1]);
                acc[3][2] = fmaf(p[j].w, f2, acc[3][2]); acc[3][3] = fmaf(p[j].w, f3, acc[3][3]);
            }
            if (++st == STAGES) { st = 0; ph ^= 1; }
        }
        float u[2][4], v[4];
#pragma unroll
        for (int h = 0; h < 2; h++)
#pragma unroll
            for (int e = 0; e < 4; e++) u[h][e] = acc[h][e] + __shfl_xor_sync(0xffffffffu, acc[h + 2][e], 16);
#pragma unroll
        for (int e = 0; e < 4; e++) v[e] = u[0][e] + __shfl_xor_sync(0xffffffffu, u[1][e], 8);
        const float ox = (b2 ? v[2] : v[0]) + __shfl_xor_sync(0xffffffffu, b2 ? v[0] : v[2], 4);
        const float oy = (b2 ? v[3] : v[1]) + __shfl_xor_sync(0xffffffffu, b2 ? v[1] : v[3], 4);
        if (seg == 1) mbar_wait(bar_mdone, 0);
        asm volatile("st.relaxed.gpu.global.v2.u32 [%0], {%1,%2};" ::"l"(ob), "r"(tagged(ox, tag)), "r"(tagged(oy, tag)) : "memory");
    }
    if (lane == 0) mbar_arrive(bar_sent);
}

}

extern "C" void kernel_launch(void* const* d_in, const int* in_sizes, int n_in, void* d_out, int out_size) {
    (void)in_sizes; (void)n_in; (void)out_size;
    static int tau = -1;
    if (tau < 0) {
        cudaFuncSetAttribute(kvq_decode_kernel, cudaFuncAttributeMaxDynamicSharedMemorySize, SMEM_BYTES);
        int dev = 0, khz = 0, bits = 0;
        cudaGetDevice(&dev);
        cudaDeviceGetAttribute(&khz, cudaDevAttrMemoryClockRate, dev);
        cudaDeviceGetAttribute(&bits, cudaDevAttrGlobalMemoryBusWidth, dev);
        const double bytes_per_ns = 2.0 * khz * 1e-6 * (bits / 8);
        tau = bytes_per_ns > 0.0 ? (int)((double)NCTA * CHUNK_BYTES / (bytes_per_ns * TAU_EFF)) : 0;
    }
    kvq_decode_kernel<<<NCTA, NTHREADS, SMEM_BYTES>>>(
        (const __nv_bfloat16*)d_in[0], (const int*)d_in[1], (const int*)d_in[2], (const __nv_bfloat16*)d_in[3],
        (const __nv_bfloat16*)d_in[4], (const __nv_bfloat16*)d_in[5], (const __nv_bfloat16*)d_in[6],
        (__nv_bfloat16*)d_out, tau);
}
```

```cpp
#include <cuda_runtime.h>
#include <cuda.h>
#include <cuda_bf16.h>
#include <stdint.h>

namespace {

constexpr int HKV = 8;
constexpr int REP = 4;
constexpr int SKV = 16384;
constexpr int DH = 128;
constexpr int NGK = 2;
constexpr int NCTA = 128;
constexpr int NG = 2;
constexpr int HPG = HKV / NG;
constexpr int CPG = NCTA / NG;
constexpr int CHUNK_TOK = 32;
constexpr int CHUNK_BYTES = CHUNK_TOK * DH * 4;
constexpr int CPS = SKV / CHUNK_TOK / CPG;
constexpr int NCH = CPS * HPG;
constexpr int TOK_PER_CTA = NCH * CHUNK_TOK;
constexpr int STAGES = 8;
constexpr int LEAD = 2;
constexpr int INFLIGHT = 4;
constexpr int STATS_START = 40;
constexpr int FWAIT = 4;
constexpr int CATCH_START = 40;
constexpr int CATCH_REF = 45;
constexpr double TAU_EFF = 0.976;
constexpr int NCW = 8;
constexpr int NCT = NCW * 32;
constexpr int NTHREADS = NCT + 64;
static_assert(CPS == NCW && HPG == 4 && CPG == 64, "layout assumptions");

constexpr int OFF_RING = 0;
constexpr int OFF_P = OFF_RING + STAGES * CHUNK_BYTES;
constexpr int OFF_PB = OFF_P + TOK_PER_CTA * REP * 4;
constexpr int OFF_QS = OFF_PB + NCH * 1024;
constexpr int OFF_CG = OFF_QS + HPG * NGK * REP * DH * 4;
constexpr int OFF_WMAX = OFF_CG + HPG * NGK * REP * 4;
constexpr int OFF_WSZ = OFF_WMAX + HPG * NCW * REP * 4;
constexpr int OFF_WB = OFF_WSZ + NCH * 8 * 4;
constexpr int OFF_F = OFF_WB + NCH * 16;
constexpr int OFF_BAR = OFF_F + HPG * REP * 16;
constexpr int NBAR = 2 * STAGES + 1 + 2 * HPG;
constexpr int SMEM_BYTES = OFF_BAR + NBAR * 8;

__device__ __align__(128) uint4 g_stat[HKV][CPG][REP];
__device__ uint32_t g_epoch[NCTA];
constexpr int BLK = 8, ACC_STRIDE = 17;
__device__ __align__(128) unsigned long long g_acc[(256 / BLK) * ACC_STRIDE * BLK];
__device__ __align__(128) float g_wide[HKV][REP * DH];
constexpr float FIX_RANGE = 16777216.f - 128.f;

__device__ __forceinline__ uint32_t smem_u32(const void* p) { return (uint32_t)__cvta_generic_to_shared(p); }
__device__ __forceinline__ void mbar_init(uint32_t bar, uint32_t cnt) {
    asm volatile("mbarrier.init.shared::cta.b64 [%0], %1;" ::"r"(bar), "r"(cnt) : "memory");
}
__device__ __forceinline__ void mbar_expect_tx(uint32_t bar, uint32_t bytes) {
    asm volatile("mbarrier.arrive.expect_tx.shared::cta.b64 _, [%0], %1;" ::"r"(bar), "r"(bytes) : "memory");
}
__device__ __forceinline__ void mbar_arrive(uint32_t bar) {
    asm volatile("mbarrier.arrive.shared::cta.b64 _, [%0];" ::"r"(bar) : "memory");
}
__device__ __forceinline__ void mbar_wait(uint32_t bar, uint32_t parity) {
    uint32_t ok;
    int it = 0;
    do {
        asm volatile(
            "{\n.reg .pred p;\nmbarrier.try_wait.parity.shared::cta.b64 p, [%1], %2;\nselp.u32 %0, 1, 0, p;\n}"
            : "=r"(ok) : "r"(bar), "r"(parity) : "memory");
    } while (!ok && ++it < (1 << 20));
}
__device__ __forceinline__ void bulk_load(uint32_t dst, const void* src, uint32_t bytes, uint32_t bar) {
    asm volatile("{\n.reg .b64 pol;\ncreatepolicy.fractional.L2::evict_first.b64 pol, 1.0;\n"
                 "cp.async.bulk.shared::cluster.global.mbarrier::complete_tx::bytes.L2::cache_hint [%0], [%1], %2, [%3], pol;\n}"
                 ::"r"(dst), "l"(src), "r"(bytes), "r"(bar) : "memory");
}
__device__ __forceinline__ void tensor_load(uint32_t dst, const CUtensorMap* tm, int row, uint32_t bar) {
    asm volatile("{\n.reg .b64 pol;\ncreatepolicy.fractional.L2::evict_first.b64 pol, 1.0;\n"
                 "cp.async.bulk.tensor.3d.shared::cluster.global.mbarrier::complete_tx::bytes.L2::cache_hint [%0], [%1, {%3, %4, %3}], [%2], pol;\n}"
                 ::"r"(dst), "l"(tm), "r"(bar), "r"(0), "r"(row) : "memory");
}
__device__ __forceinline__ int2 lds_i2(uint32_t a) {
    int2 v;
    asm volatile("ld.shared.v2.s32 {%0,%1}, [%2];" : "=r"(v.x), "=r"(v.y) : "r"(a) : "memory");
    return v;
}
__device__ __forceinline__ void mma_tf32(float (&d)[4], float a0, float a1, float a2, float a3, float b0, float b1) {
    asm volatile("mma.sync.aligned.m16n8k8.row.col.f32.tf32.tf32.f32 {%0,%1,%2,%3}, {%4,%5,%6,%7}, {%8,%9}, {%0,%1,%2,%3};"
                 : "+f"(d[0]), "+f"(d[1]), "+f"(d[2]), "+f"(d[3])
                 : "r"(__float_as_uint(a0)), "r"(__float_as_uint(a1)), "r"(__float_as_uint(a2)), "r"(__float_as_uint(a3)),
                   "r"(__float_as_uint(b0)), "r"(__float_as_uint(b1)));
}
__device__ __forceinline__ float tf32_trunc(float v) { return __uint_as_float(__float_as_uint(v) & 0xffffe000u); }
__device__ __forceinline__ int4 lds_i4(uint32_t a) {
    int4 v;
    asm volatile("ld.shared.v4.s32 {%0,%1,%2,%3}, [%4];" : "=r"(v.x), "=r"(v.y), "=r"(v.z), "=r"(v.w) : "r"(a) : "memory");
    return v;
}
__device__ __forceinline__ float4 lds_f4(uint32_t a) {
    float4 v;
    asm volatile("ld.shared.v4.f32 {%0,%1,%2,%3}, [%4];" : "=f"(v.x), "=f"(v.y), "=f"(v.z), "=f"(v.w) : "r"(a) : "memory");
    return v;
}
__device__ __forceinline__ void consumer_bar() { asm volatile("bar.sync 1, %0;" ::"n"(NCT) : "memory"); }
__device__ __forceinline__ float ex2(float x) {
    float y;
    asm("ex2.approx.ftz.f32 %0, %1;" : "=f"(y) : "f"(x));
    return y;
}
__device__ __forceinline__ uint32_t gtime32() {
    uint32_t t;
    asm volatile("mov.u32 %0, %%globaltimer_lo;" : "=r"(t));
    return t;
}
__device__ __forceinline__ float untag(uint32_t w) { return __uint_as_float(w & ~3u); }
__device__ __forceinline__ uint32_t mism4(const uint4& w, uint32_t tag) {
    return ((w.x ^ tag) | (w.y ^ tag)) | ((w.z ^ tag) | (w.w ^ tag));
}

__device__ __noinline__ unsigned long long wide_add(unsigned long long* pacc, float* pw, float a, float b) {
    atomicAdd(pw, a);
    atomicAdd(pw + 1, b);
    __threadfence();
    return atomicAdd(pacc, (1ull << 7) + 1ull) + (1ull << 7) + 1ull;
}
__device__ __noinline__ void wide_finish(__nv_bfloat162* pout, const volatile float* pw, float a, float b) {
    __threadfence();
    *pout = __floats2bfloat162_rn(a + pw[0], b + pw[1]);
}

__global__ void __launch_bounds__(NTHREADS, 1)
kvq_decode_kernel(const __nv_bfloat16* __restrict__ q, const int* __restrict__ qk, const __grid_constant__ CUtensorMap vmap,
                  const __nv_bfloat16* __restrict__ k_scales, const __nv_bfloat16* __restrict__ k_zeros,
                  const __nv_bfloat16* __restrict__ v_scales, const __nv_bfloat16* __restrict__ v_zeros,
                  __nv_bfloat16* __restrict__ out, int tau) {
    extern __shared__ __align__(1024) unsigned char smem[];
    const uint32_t sb = smem_u32(smem);
    const int grp = blockIdx.x & (NG - 1);
    const int r = blockIdx.x / NG;
    const int head0 = grp * HPG;
    const uint32_t bar_full = sb + OFF_BAR, bar_empty = bar_full + STAGES * 8, bar_go = bar_empty + STAGES * 8;
    const uint32_t bar_own = bar_go + 8, bar_fready = bar_own + HPG * 8;
    const size_t base = ((size_t)head0 * (SKV / CHUNK_TOK) + r) * CHUNK_BYTES;
    const char* ksrc = (const char*)qk + base;
    uint32_t tnext = 0;

    if (threadIdx.x == 0) {
        tnext = gtime32() + tau;
#pragma unroll
        for (int i = 0; i < LEAD; i++) mbar_init(bar_full + i * 8, 1);
        asm volatile("fence.proxy.async.shared::cta;" ::: "memory");
#pragma unroll
        for (int i = 0; i < LEAD; i++) {
            mbar_expect_tx(bar_full + i * 8, CHUNK_BYTES);
            bulk_load(sb + OFF_RING + i * CHUNK_BYTES, ksrc + (size_t)i * CPG * CHUNK_BYTES, CHUNK_BYTES, bar_full + i * 8);
        }
#pragma unroll
        for (int i = LEAD; i < STAGES; i++) mbar_init(bar_full + i * 8, 1);
#pragma unroll
        for (int i = 0; i < STAGES; i++) mbar_init(bar_empty + i * 8, NCW);
        mbar_init(bar_go, 1);
#pragma unroll
        for (int i = 0; i < HPG; i++) {
            mbar_init(bar_own + i * 8, NCW);
            mbar_init(bar_fready + i * 8, 1);
        }
        asm volatile("fence.proxy.async.shared::cta;" ::: "memory");
    }
    const int lane = threadIdx.x & 31;

    if (threadIdx.x < 32) {
        __syncwarp();
        asm volatile("bar.arrive 2, %0;" ::"n"(NTHREADS) : "memory");
        if (lane == 0) {
            asm volatile("prefetch.tensormap [%0];" ::"l"(&vmap) : "memory");
            const int vrow0 = head0 * SKV + r * CHUNK_TOK;
            const uint32_t tstart = tnext - tau;
            uint32_t t1 = gtime32(), t2 = t1;
            for (int it = 0; it < 4096 && t2 == t1; it++) t2 = gtime32();
            t1 = t2;
            for (int it = 0; it < 4096 && t2 == t1; it++) t2 = gtime32();
            const int tick = (int)(t2 - t1);
            if (tick == 0) tau = 0;
            int st = LEAD % STAGES, ph = (LEAD / STAGES) & 1;
            for (int i = LEAD; i < 2 * NCH; i++) {
                if (i >= INFLIGHT) mbar_wait(bar_full + ((i - INFLIGHT) % STAGES) * 8, ((i - INFLIGHT) / STAGES) & 1);
                if (i >= STAGES) mbar_wait(bar_empty + st * 8, ph ^ 1);
                if (tau > 0) {
                    uint32_t now = gtime32();
                    for (int it = 0; it < (1 << 16) && (int)(now - tnext) < 0; it++) now = gtime32();
                    if ((int)(now - tnext) > tick) tnext = now - tick;
                    tnext += tau;
                    if (i >= CATCH_START) {
                        const int lag = (int)(now - tstart) - (i - LEAD + 1) * (tau + tau / CATCH_REF);
                        tnext -= min(max(lag / 4, 0), tau / 5);
                    }
                }
                mbar_expect_tx(bar_full + st * 8, CHUNK_BYTES);
                if (i < NCH) bulk_load(sb + OFF_RING + st * CHUNK_BYTES, ksrc + (size_t)i * CPG * CHUNK_BYTES, CHUNK_BYTES, bar_full + st * 8);
                else tensor_load(sb + OFF_RING + st * CHUNK_BYTES, &vmap, vrow0 + (i - NCH) * CPG * CHUNK_TOK, bar_full + st * 8);
                if (i == STATS_START) mbar_arrive(bar_go);
                if (++st == STAGES) { st = 0; ph ^= 1; }
            }
        }
        return;
    }
    if (threadIdx.x < 64) {
        const float* s_wmax = (const float*)(smem + OFF_WMAX);
        const float* s_wsz = (const float*)(smem + OFF_WSZ);
        const float* s_wb = (const float*)(smem + OFF_WB);
        float4* s_f = (float4*)(smem + OFF_F);
        const uint32_t par = (g_epoch[blockIdx.x] + 1u) & 1u;
        if (lane < 16) { const int id = r * 16 + lane; g_acc[((id / (4 * BLK)) * ACC_STRIDE + head0) * BLK + id % (4 * BLK)] = 0ull; }
        else *(float2*)(&g_wide[head0][0] + r * 32 + (lane - 16) * 2) = make_float2(0.f, 0.f);
        __syncwarp();
        if (lane == 0) g_epoch[blockIdx.x] = par;
        asm volatile("bar.sync 2, %0;" ::"n"(NTHREADS) : "memory");
        __threadfence();
        float m_prev = 0.f, b_prev = 0.f;
#pragma unroll 1
        for (int step = 0; step <= HPG; step++) {
            const float m_own = m_prev, b_own = b_prev;
            if (step < HPG) {
                mbar_wait(bar_own + step * 8, 0);
                const int h = lane & 3;
                float mo = -INFINITY, lo = 0.f, bo = 0.f;
#pragma unroll
                for (int c = 0; c < CPS; c++) {
                    lo += s_wsz[(step * CPS + c) * 8 + h];
                    bo += s_wb[(step * CPS + c) * REP + h];
                    mo = fmaxf(mo, s_wmax[(step * NCW + c) * REP + h]);
                }
                m_prev = untag(__float_as_uint(mo));
                b_prev = untag(__float_as_uint(bo));
                if (lane < REP)
                    asm volatile("st.relaxed.gpu.global.v4.u32 [%0], {%1,%2,%3,%4};" ::"l"(&g_stat[head0 + step][r][h]),
                                 "r"(__float_as_uint(m_prev) | par), "r"((__float_as_uint(lo) & ~3u) | par),
                                 "r"(__float_as_uint(b_prev) | par), "r"(par) : "memory");
                if (step == 0) continue;
            } else {
                mbar_wait(bar_go, 0);
            }
            const int seg = step - 1;
            constexpr int NS = CPG / 8;
            const uint4* gs = &g_stat[head0 + seg][0][0] + lane;
            uint4 w[NS];
            for (int it = 0; it < (1 << 20); it++) {
                uint32_t miss = 0u;
#pragma unroll
                for (int k = 0; k < NS; k++) {
                    asm volatile("ld.relaxed.gpu.global.v4.u32 {%0,%1,%2,%3}, [%4];"
                                 : "=r"(w[k].x), "=r"(w[k].y), "=r"(w[k].z), "=r"(w[k].w) : "l"(gs + 32 * k) : "memory");
                    miss |= mism4(w[k], par);
                }
                if (__all_sync(0xffffffffu, (miss & 3u) == 0u)) break;
                __nanosleep(300);
            }
            if (seg == 0) __threadfence();
            float M = untag(w[0].x);
#pragma unroll
            for (int k = 1; k < NS; k++) M = fmaxf(M, untag(w[k].x));
#pragma unroll
            for (int o = 4; o <= 16; o <<= 1) M = fmaxf(M, __shfl_xor_sync(0xffffffffu, M, o));
            float L = 0.f, W = 0.f;
#pragma unroll
            for (int k = 0; k < NS; k++) {
                const float e = ex2(untag(w[k].x) - M);
                L = fmaf(e, untag(w[k].y), L);
                W = fmaf(e, untag(w[k].z), W);
            }
#pragma unroll
            for (int o = 4; o <= 16; o <<= 1) {
                L += __shfl_xor_sync(0xffffffffu, L, o);
                W += __shfl_xor_sync(0xffffffffu, W, o);
            }
            const float e_own = ex2(m_own - M);
            float unit = W / L * (1.f / FIX_RANGE);
            float fs = e_own / W * FIX_RANGE;
            float lim = fs * b_own * 0.999f;
            if (!(unit > 1e-30f && unit < 1e30f)) { lim = -1.f; unit = 0.f; }
            if (lane < 4) s_f[seg * REP + lane] = make_float4(fs, lim, unit, e_own / L);
            __syncwarp();
            if (lane == 0) mbar_arrive(bar_fready + seg * 8);
        }
        return;
    }

    const int tid = threadIdx.x - 64;
    const int warp = tid >> 5;
    float* s_p = (float*)(smem + OFF_P);
    float* s_qs = (float*)(smem + OFF_QS);
    float* s_cg = (float*)(smem + OFF_CG);
    float* s_wmax = (float*)(smem + OFF_WMAX);
    float* s_wsz = (float*)(smem + OFF_WSZ);

    {
        const int kg = warp >> 2, h = warp & 3;
        const float qscale = 0.08838834764831845f * 1.4426950408889634f;
        uint2 qq[HPG], ss[HPG], zz[HPG];
#pragma unroll
        for (int seg = 0; seg < HPG; seg++) {
            qq[seg] = *(const uint2*)(q + ((head0 + seg) * REP + h) * DH + lane * 4);
            ss[seg] = *(const uint2*)(k_scales + ((head0 + seg) * NGK + kg) * DH + lane * 4);
            zz[seg] = *(const uint2*)(k_zeros + ((head0 + seg) * NGK + kg) * DH + lane * 4);
        }
#pragma unroll
        for (int seg = 0; seg < HPG; seg++) {
            float4 a;
            a.x = __uint_as_float(qq[seg].x << 16) * __uint_as_float(ss[seg].x << 16) * qscale;
            a.y = __uint_as_float(qq[seg].x & 0xffff0000u) * __uint_as_float(ss[seg].x & 0xffff0000u) * qscale;
            a.z = __uint_as_float(qq[seg].y << 16) * __uint_as_float(ss[seg].y << 16) * qscale;
            a.w = __uint_as_float(qq[seg].y & 0xffff0000u) * __uint_as_float(ss[seg].y & 0xffff0000u) * qscale;
            float c = a.x * __uint_as_float(zz[seg].x << 16) + a.y * __uint_as_float(zz[seg].x & 0xffff0000u) +
                      a.z * __uint_as_float(zz[seg].y << 16) + a.w * __uint_as_float(zz[seg].y & 0xffff0000u);
#pragma unroll
            for (int o = 16; o > 0; o >>= 1) c += __shfl_xor_sync(0xffffffffu, c, o);
            *(float4*)(s_qs + (seg * NCW + warp) * DH + lane * 4) = a;
            if (lane == 0) s_cg[seg * NCW + warp] = c;
        }
    }
    uint32_t vsb[HPG], vzb[HPG];
#pragma unroll
    for (int i = 0; i < HPG; i++) {
        const int tok = (head0 + i) * SKV + (warp * CPG + r) * CHUNK_TOK + lane;
        vsb[i] = ((const uint16_t*)v_scales)[tok];
        vzb[i] = ((const uint16_t*)v_zeros)[tok];
    }
    asm volatile("bar.sync 2, %0;" ::"n"(NTHREADS) : "memory");

    int st = 0, ph = 0;
    {
        const int myh = (lane >> 1) & 3;
        const bool b2 = lane & 4, b1 = lane & 2;
        const uint32_t xoff = sb + OFF_RING + (warp * 4 + (lane >> 3)) * (DH * 4) + (lane & 7) * 16;
        float mrun = -INFINITY;
#pragma unroll 1
        for (int sg = 0; sg < HPG * NGK; sg++) {
            float4 qr[REP][4];
#pragma unroll
            for (int h = 0; h < REP; h++)
#pragma unroll
                for (int j = 0; j < 4; j++)
                    qr[h][j] = *(const float4*)(s_qs + (sg * REP + h) * DH + ((lane & 7) + 8 * j) * 4);
            const float cg = s_cg[sg * REP + myh];
#pragma unroll 1
            for (int c = sg * (CPS / NGK); c < (sg + 1) * (CPS / NGK); c++) {
                mbar_wait(bar_full + st * 8, ph);
                const uint32_t xa = xoff + st * CHUNK_BYTES;
                int4 x[4];
#pragma unroll
                for (int j = 0; j < 4; j++) x[j] = lds_i4(xa + j * 128);
                __syncwarp();
                if (lane == 0) mbar_arrive(bar_empty + st * 8);
                float s[REP] = {0.f, 0.f, 0.f, 0.f};
#pragma unroll
                for (int j = 0; j < 4; j++) {
                    const float f0 = (float)x[j].x, f1 = (float)x[j].y, f2 = (float)x[j].z, f3 = (float)x[j].w;
#pragma unroll
                    for (int h = 0; h < REP; h++) {
                        s[h] = fmaf(qr[h][j].x, f0, s[h]);
                        s[h] = fmaf(qr[h][j].y, f1, s[h]);
                        s[h] = fmaf(qr[h][j].z, f2, s[h]);
                        s[h] = fmaf(qr[h][j].w, f3, s[h]);
                    }
                }
                float k0 = (b2 ? s[2] : s[0]) + __shfl_xor_sync(0xffffffffu, b2 ? s[0] : s[2], 4);
                float k1 = (b2 ? s[3] : s[1]) + __shfl_xor_sync(0xffffffffu, b2 ? s[1] : s[3], 4);
                float t = (b1 ? k1 : k0) + __shfl_xor_sync(0xffffffffu, b1 ? k0 : k1, 2);
                t += __shfl_xor_sync(0xffffffffu, t, 1);
                t -= cg;
                if (!(lane & 1)) s_p[c * (CHUNK_TOK * REP) + warp * 16 + (lane >> 1)] = t;
                mrun = fmaxf(mrun, t);
                if (++st == STAGES) { st = 0; ph ^= 1; }
            }
            if (sg & 1) {
                mrun = fmaxf(mrun, __shfl_xor_sync(0xffffffffu, mrun, 8));
                mrun = fmaxf(mrun, __shfl_xor_sync(0xffffffffu, mrun, 16));
                if (lane < 8 && !(lane & 1)) s_wmax[((sg >> 1) * NCW + warp) * REP + myh] = mrun;
                mrun = -INFINITY;
                consumer_bar();
                const int i = sg >> 1;
                float4 M = *(const float4*)(s_wmax + i * NCW * REP);
#pragma unroll
                for (int w = 1; w < NCW; w++) {
                    const float4 m = *(const float4*)(s_wmax + (i * NCW + w) * REP);
                    M.x = fmaxf(M.x, m.x); M.y = fmaxf(M.y, m.y); M.z = fmaxf(M.z, m.z); M.w = fmaxf(M.w, m.w);
                }
                M.x = untag(__float_as_uint(M.x)); M.y = untag(__float_as_uint(M.y));
                M.z = untag(__float_as_uint(M.z)); M.w = untag(__float_as_uint(M.w));
                const float vs = __uint_as_float(vsb[0] << 16), vz = __uint_as_float(vzb[0] << 16);
#pragma unroll
                for (int k = 0; k + 1 < HPG; k++) { vsb[k] = vsb[k + 1]; vzb[k] = vzb[k + 1]; }
                float4 p = *(const float4*)(s_p + (tid + i * NCT) * REP);
                p.x = ex2(p.x - M.x); p.y = ex2(p.y - M.y); p.z = ex2(p.z - M.z); p.w = ex2(p.w - M.w);
                const float4 l = p;
                p.x *= vs; p.y *= vs; p.z *= vs; p.w *= vs;
                const float4 hi = make_float4(tf32_trunc(p.x), tf32_trunc(p.y), tf32_trunc(p.z), tf32_trunc(p.w));
                const float4 lo = make_float4(tf32_trunc(p.x - hi.x), tf32_trunc(p.y - hi.y), tf32_trunc(p.z - hi.z), tf32_trunc(p.w - hi.w));
                const float4 z = make_float4((hi.x + lo.x) * vz, (hi.y + lo.y) * vz, (hi.z + lo.z) * vz, (hi.w + lo.w) * vz);
                {
                    float* pb = (float*)(smem + OFF_PB) + (i * NCW + warp) * 256 + (lane >> 4) * 128 + ((lane & 7) >> 1) * 4 +
                                ((lane >> 3) & 1) * 2 + (lane & 1);
                    pb[0 * 16] = hi.x; pb[1 * 16] = lo.x; pb[2 * 16] = hi.y; pb[3 * 16] = lo.y;
                    pb[4 * 16] = hi.z; pb[5 * 16] = lo.z; pb[6 * 16] = hi.w; pb[7 * 16] = lo.w;
                }
                const bool b4 = lane & 16, b3 = lane & 8;
                const float u0 = (b4 ? z.x : l.x) + __shfl_xor_sync(0xffffffffu, b4 ? l.x : z.x, 16);
                const float u1 = (b4 ? z.y : l.y) + __shfl_xor_sync(0xffffffffu, b4 ? l.y : z.y, 16);
                const float u2 = (b4 ? z.z : l.z) + __shfl_xor_sync(0xffffffffu, b4 ? l.z : z.z, 16);
                const float u3 = (b4 ? z.w : l.w) + __shfl_xor_sync(0xffffffffu, b4 ? l.w : z.w, 16);
                const float v0 = (b3 ? u2 : u0) + __shfl_xor_sync(0xffffffffu, b3 ? u0 : u2, 8);
                const float v1 = (b3 ? u3 : u1) + __shfl_xor_sync(0xffffffffu, b3 ? u1 : u3, 8);
                float t = (b2 ? v1 : v0) + __shfl_xor_sync(0xffffffffu, b2 ? v0 : v1, 4);
                t += __shfl_xor_sync(0xffffffffu, t, 2);
                t += __shfl_xor_sync(0xffffffffu, t, 1);
                if (!(lane & 3)) s_wsz[(i * NCW + warp) * 8 + (lane >> 2)] = t;
                const float wv = fabsf(vs) * (16.f + fabsf(vz));
                const float y0 = (b4 ? l.z : l.x) * wv + __shfl_xor_sync(0xffffffffu, (b4 ? l.x : l.z) * wv, 16);
                const float y1 = (b4 ? l.w : l.y) * wv + __shfl_xor_sync(0xffffffffu, (b4 ? l.y : l.w) * wv, 16);
                float y = (b3 ? y1 : y0) + __shfl_xor_sync(0xffffffffu, b3 ? y0 : y1, 8);
#pragma unroll
                for (int o = 4; o > 0; o >>= 1) y += __shfl_xor_sync(0xffffffffu, y, o);
                if (!(lane & 7)) ((float*)(smem + OFF_WB))[(i * NCW + warp) * REP + (lane >> 3)] = y;
                __syncwarp();
                if (lane == 0) mbar_arrive(bar_own + i * 8);
            }
        }
    }

    const int g = lane >> 2, t = lane & 3;
    const int oidx = t * DH + warp * 16 + g * 2;
    unsigned long long* pacc = &g_acc[((tid / BLK) * ACC_STRIDE + head0) * BLK + tid % BLK];
    __nv_bfloat162* pout = (__nv_bfloat162*)(out + head0 * (REP * DH) + oidx);
    const uint32_t piece = (warp & 1) * 4 + (g >> 1);
    const uint32_t xoff0 = sb + OFF_RING + (warp >> 1) * 4096 + (2 * t) * 128 + ((piece ^ (2 * t)) << 4) + (g & 1) * 8;
    const uint32_t xoff1 = sb + OFF_RING + (warp >> 1) * 4096 + (2 * t + 1) * 128 + ((piece ^ (2 * t + 1)) << 4) + (g & 1) * 8;
    uint32_t pa = sb + OFF_PB + lane * 16;
#pragma unroll 1
    for (int seg = 0; seg < HPG; seg++) {
        mbar_wait(bar_own + seg * 8, 0);
        float zc = 0.f;
#pragma unroll
        for (int c = 0; c < CPS; c++) zc += s_wsz[(seg * CPS + c) * 8 + 4 + t];
        float d0[4] = {-0.5f * zc, 0.f, -0.5f * zc, 0.f}, d1[4] = {-0.5f * zc, 0.f, -0.5f * zc, 0.f};
        float4 fz;
#pragma unroll 1
        for (int c = 0; c < CPS; c++) {
            const float4 pA = lds_f4(pa), pB = lds_f4(pa + 512);
            pa += 1024;
            uint32_t xa0 = xoff0 + st * CHUNK_BYTES, xa1 = xoff1 + st * CHUNK_BYTES;
            asm volatile("" : "+r"(xa0), "+r"(xa1));
            if (c == FWAIT) {
                mbar_wait(bar_fready + seg * 8, 0);
                fz = lds_f4(sb + OFF_F + (seg * REP + t) * 16);
            }
            mbar_wait(bar_full + st * 8, ph);
            int2 x[4][2];
#pragma unroll
            for (int s = 0; s < 4; s++) {
                x[s][0] = lds_i2(xa0 + s * 1024);
                x[s][1] = lds_i2(xa1 + s * 1024);
            }
            __syncwarp();
            if (lane == 0) mbar_arrive(bar_empty + st * 8);
            mma_tf32(d0, (float)x[0][0].x, (float)x[0][0].y, (float)x[0][1].x, (float)x[0][1].y, pA.x, pA.y);
            mma_tf32(d1, (float)x[1][0].x, (float)x[1][0].y, (float)x[1][1].x, (float)x[1][1].y, pA.z, pA.w);
            mma_tf32(d0, (float)x[2][0].x, (float)x[2][0].y, (float)x[2][1].x, (float)x[2][1].y, pB.x, pB.y);
            mma_tf32(d1, (float)x[3][0].x, (float)x[3][0].y, (float)x[3][1].x, (float)x[3][1].y, pB.z, pB.w);
            if (++st == STAGES) { st = 0; ph ^= 1; }
        }
        const float ox = (d0[0] + d0[1]) + (d1[0] + d1[1]);
        const float oy = (d0[2] + d0[3]) + (d1[2] + d1[3]);
        const float ya = ox * fz.x, yb = oy * fz.x;
        unsigned long long op = ((unsigned long long)(long long)__float2int_rn(ya) << 39) +
                                ((unsigned long long)(long long)__float2int_rn(yb) << 14) + 1ull;
        const bool wide = !(fabsf(ya) <= fz.y) | !(fabsf(yb) <= fz.y);
        unsigned long long tot = 0ull;
        asm volatile("{\n.reg .pred p;\nsetp.eq.u32 p, %3, 0;\n@p atom.relaxed.gpu.global.add.u64 %0, [%1], %2;\n}"
                     : "+l"(tot) : "l"(pacc), "l"(op), "r"((uint32_t)wide) : "memory");
        if (__builtin_expect(wide, 0)) op = wide_add(pacc, &g_wide[head0 + seg][oidx], ox * fz.w, oy * fz.w);
        tot += op;
        const int vb = (int)((long long)(tot << 25) >> 39);
        const int va = ((int)(tot >> 32) + 64) >> 7;
        const float oa = (float)va * fz.z, ob = (float)vb * fz.z;
        const uint32_t low = (uint32_t)tot & 0x3fffu;
        const __nv_bfloat162 o2 = __floats2bfloat162_rn(oa, ob);
        asm volatile("{\n.reg .pred p;\nsetp.eq.u32 p, %2, %3;\n@p st.global.u32 [%0], %1;\n}"
                     ::"l"(pout), "r"(*(const uint32_t*)&o2), "r"(low), "n"(CPG) : "memory");
        if (__builtin_expect(low > CPG && (low & 127u) == CPG, 0)) wide_finish(pout, &g_wide[head0 + seg][oidx], oa, ob);
        pacc += BLK;
        pout += REP * DH / 2;
    }
}

}

typedef CUresult (*EncodeTiledFn)(CUtensorMap*, CUtensorMapDataType, cuuint32_t, void*, const cuuint64_t*, const cuuint64_t*,
                                  const cuuint32_t*, const cuuint32_t*, CUtensorMapInterleave, CUtensorMapSwizzle,
                                  CUtensorMapL2promotion, CUtensorMapFloatOOBfill);

extern "C" void kernel_launch(void* const* d_in, const int* in_sizes, int n_in, void* d_out, int out_size) {
    (void)in_sizes; (void)n_in; (void)out_size;
    static int tau = -1;
    static EncodeTiledFn encode = nullptr;
    if (tau < 0) {
        cudaFuncSetAttribute(kvq_decode_kernel, cudaFuncAttributeMaxDynamicSharedMemorySize, SMEM_BYTES);
        int dev = 0, khz = 0, bits = 0;
        cudaGetDevice(&dev);
        cudaDeviceGetAttribute(&khz, cudaDevAttrMemoryClockRate, dev);
        cudaDeviceGetAttribute(&bits, cudaDevAttrGlobalMemoryBusWidth, dev);
        const double bytes_per_ns = 2.0 * khz * 1e-6 * (bits / 8);
        tau = bytes_per_ns > 0.0 ? (int)((double)NCTA * CHUNK_BYTES / (bytes_per_ns * TAU_EFF)) : 0;
        void* fn = nullptr;
        cudaDriverEntryPointQueryResult qr;
        cudaGetDriverEntryPoint("cuTensorMapEncodeTiled", &fn, cudaEnableDefault, &qr);
        encode = (EncodeTiledFn)fn;
    }
    CUtensorMap vmap;
    const cuuint64_t dims[3] = {32, (cuuint64_t)HKV * SKV, 4}, strides[2] = {DH * 4, 128};
    const cuuint32_t box[3] = {32, CHUNK_TOK, 4}, estr[3] = {1, 1, 1};
    encode(&vmap, CU_TENSOR_MAP_DATA_TYPE_INT32, 3, d_in[2], dims, strides, box, estr, CU_TENSOR_MAP_INTERLEAVE_NONE,
           CU_TENSOR_MAP_SWIZZLE_128B, CU_TENSOR_MAP_L2_PROMOTION_NONE, CU_TENSOR_MAP_FLOAT_OOB_FILL_NONE);
    kvq_decode_kernel<<<NCTA, NTHREADS, SMEM_BYTES>>>(
        (const __nv_bfloat16*)d_in[0], (const int*)d_in[1], vmap, (const __nv_bfloat16*)d_in[3],
        (const __nv_bfloat16*)d_in[4], (const __nv_bfloat16*)d_in[5], (const __nv_bfloat16*)d_in[6],
        (__nv_bfloat16*)d_out, tau);
}
```

```cpp
#include <cuda_runtime.h>
#include <cuda.h>
#include <cuda_bf16.h>
#include <stdint.h>

namespace {

constexpr int HKV = 8;
constexpr int REP = 4;
constexpr int SKV = 16384;
constexpr int DH = 128;
constexpr int NGK = 2;
constexpr int NCTA = 128;
constexpr int NG = 2;
constexpr int HPG = HKV / NG;
constexpr int CPG = NCTA / NG;
constexpr int CHUNK_TOK = 32;
constexpr int CHUNK_BYTES = CHUNK_TOK * DH * 4;
constexpr int CPS = SKV / CHUNK_TOK / CPG;
constexpr int NCH = CPS * HPG;
constexpr int TOK_PER_CTA = NCH * CHUNK_TOK;
constexpr int STAGES = 8;
constexpr int LEAD = 2;
constexpr int INFLIGHT = 4;
constexpr int STATS_START = 40;
constexpr int FWAIT = 4;
constexpr int CATCH_START = 40;
constexpr int CATCH_REF = 54;
constexpr double TAU_EFF = 0.973;
constexpr int NCW = 8;
constexpr int NCT = NCW * 32;
constexpr int NTHREADS = NCT + 64;
static_assert(CPS == NCW && HPG == 4 && CPG == 64, "layout assumptions");

constexpr int OFF_RING = 0;
constexpr int OFF_P = OFF_RING + STAGES * CHUNK_BYTES;
constexpr int OFF_PB = OFF_P + TOK_PER_CTA * REP * 4;
constexpr int OFF_QS = OFF_PB + NCH * 1024;
constexpr int OFF_CG = OFF_QS + HPG * NGK * REP * DH * 4;
constexpr int OFF_WMAX = OFF_CG + HPG * NGK * REP * 4;
constexpr int OFF_WSZ = OFF_WMAX + HPG * NCW * REP * 4;
constexpr int OFF_WB = OFF_WSZ + NCH * 8 * 4;
constexpr int OFF_F = OFF_WB + NCH * 16;
constexpr int OFF_BAR = OFF_F + HPG * REP * 16;
constexpr int NBAR = 2 * STAGES + 1 + 2 * HPG;
constexpr int SMEM_BYTES = OFF_BAR + NBAR * 8;

__device__ __align__(128) uint4 g_stat[HKV][CPG][REP];
__device__ uint32_t g_epoch[NCTA];
constexpr int BLK = 8, ACC_STRIDE = 17;
__device__ __align__(128) unsigned long long g_acc[(256 / BLK) * ACC_STRIDE * BLK];
__device__ __align__(128) float g_wide[HKV][REP * DH];
constexpr float FIX_RANGE = 16777216.f - 128.f;

__device__ __forceinline__ uint32_t smem_u32(const void* p) { return (uint32_t)__cvta_generic_to_shared(p); }
__device__ __forceinline__ void mbar_init(uint32_t bar, uint32_t cnt) {
    asm volatile("mbarrier.init.shared::cta.b64 [%0], %1;" ::"r"(bar), "r"(cnt) : "memory");
}
__device__ __forceinline__ void mbar_expect_tx(uint32_t bar, uint32_t bytes) {
    asm volatile("mbarrier.arrive.expect_tx.shared::cta.b64 _, [%0], %1;" ::"r"(bar), "r"(bytes) : "memory");
}
__device__ __forceinline__ void mbar_arrive(uint32_t bar) {
    asm volatile("mbarrier.arrive.shared::cta.b64 _, [%0];" ::"r"(bar) : "memory");
}
__device__ __forceinline__ void mbar_wait(uint32_t bar, uint32_t parity) {
    uint32_t ok;
    int it = 0;
    do {
        asm volatile(
            "{\n.reg .pred p;\nmbarrier.try_wait.parity.shared::cta.b64 p, [%1], %2;\nselp.u32 %0, 1, 0, p;\n}"
            : "=r"(ok) : "r"(bar), "r"(parity) : "memory");
    } while (!ok && ++it < (1 << 20));
}
__device__ __forceinline__ void bulk_load(uint32_t dst, const void* src, uint32_t bytes, uint32_t bar) {
    asm volatile("{\n.reg .b64 pol;\ncreatepolicy.fractional.L2::evict_first.b64 pol, 1.0;\n"
                 "cp.async.bulk.shared::cluster.global.mbarrier::complete_tx::bytes.L2::cache_hint [%0], [%1], %2, [%3], pol;\n}"
                 ::"r"(dst), "l"(src), "r"(bytes), "r"(bar) : "memory");
}
__device__ __forceinline__ void tensor_load(uint32_t dst, const CUtensorMap* tm, int row, uint32_t bar) {
    asm volatile("{\n.reg .b64 pol;\ncreatepolicy.fractional.L2::evict_first.b64 pol, 1.0;\n"
                 "cp.async.bulk.tensor.3d.shared::cluster.global.mbarrier::complete_tx::bytes.L2::cache_hint [%0], [%1, {%3, %4, %3}], [%2], pol;\n}"
                 ::"r"(dst), "l"(tm), "r"(bar), "r"(0), "r"(row) : "memory");
}
__device__ __forceinline__ int2 lds_i2(uint32_t a) {
    int2 v;
    asm volatile("ld.shared.v2.s32 {%0,%1}, [%2];" : "=r"(v.x), "=r"(v.y) : "r"(a) : "memory");
    return v;
}
__device__ __forceinline__ void mma_tf32(float (&d)[4], float a0, float a1, float a2, float a3, float b0, float b1) {
    asm volatile("mma.sync.aligned.m16n8k8.row.col.f32.tf32.tf32.f32 {%0,%1,%2,%3}, {%4,%5,%6,%7}, {%8,%9}, {%0,%1,%2,%3};"
                 : "+f"(d[0]), "+f"(d[1]), "+f"(d[2]), "+f"(d[3])
                 : "r"(__float_as_uint(a0)), "r"(__float_as_uint(a1)), "r"(__float_as_uint(a2)), "r"(__float_as_uint(a3)),
                   "r"(__float_as_uint(b0)), "r"(__float_as_uint(b1)));
}
__device__ __forceinline__ float tf32_trunc(float v) { return __uint_as_float(__float_as_uint(v) & 0xffffe000u); }
__device__ __forceinline__ int4 lds_i4(uint32_t a) {
    int4 v;
    asm volatile("ld.shared.v4.s32 {%0,%1,%2,%3}, [%4];" : "=r"(v.x), "=r"(v.y), "=r"(v.z), "=r"(v.w) : "r"(a) : "memory");
    return v;
}
__device__ __forceinline__ float4 lds_f4(uint32_t a) {
    float4 v;
    asm volatile("ld.shared.v4.f32 {%0,%1,%2,%3}, [%4];" : "=f"(v.x), "=f"(v.y), "=f"(v.z), "=f"(v.w) : "r"(a) : "memory");
    return v;
}
__device__ __forceinline__ void consumer_bar() { asm volatile("bar.sync 1, %0;" ::"n"(NCT) : "memory"); }
__device__ __forceinline__ float ex2(float x) {
    float y;
    asm("ex2.approx.ftz.f32 %0, %1;" : "=f"(y) : "f"(x));
    return y;
}
__device__ __forceinline__ uint32_t gtime32() {
    uint32_t t;
    asm volatile("mov.u32 %0, %%globaltimer_lo;" : "=r"(t));
    return t;
}
__device__ __forceinline__ float untag(uint32_t w) { return __uint_as_float(w & ~3u); }
__device__ __forceinline__ uint32_t mism4(const uint4& w, uint32_t tag) {
    return ((w.x ^ tag) | (w.y ^ tag)) | ((w.z ^ tag) | (w.w ^ tag));
}

__device__ __noinline__ unsigned long long wide_add(unsigned long long* pacc, float* pw, float a, float b) {
    atomicAdd(pw, a);
    atomicAdd(pw + 1, b);
    __threadfence();
    return atomicAdd(pacc, (1ull << 7) + 1ull) + (1ull << 7) + 1ull;
}
__device__ __noinline__ void wide_finish(__nv_bfloat162* pout, const volatile float* pw, float a, float b) {
    __threadfence();
    *pout = __floats2bfloat162_rn(a + pw[0], b + pw[1]);
}

__global__ void __launch_bounds__(NTHREADS, 1)
kvq_decode_kernel(const __nv_bfloat16* __restrict__ q, const int* __restrict__ qk, const __grid_constant__ CUtensorMap vmap,
                  const __nv_bfloat16* __restrict__ k_scales, const __nv_bfloat16* __restrict__ k_zeros,
                  const __nv_bfloat16* __restrict__ v_scales, const __nv_bfloat16* __restrict__ v_zeros,
                  __nv_bfloat16* __restrict__ out, int tau) {
    extern __shared__ __align__(1024) unsigned char smem[];
    const uint32_t sb = smem_u32(smem);
    const int grp = blockIdx.x & (NG - 1);
    const int r = blockIdx.x / NG;
    const int head0 = grp * HPG;
    const uint32_t bar_full = sb + OFF_BAR, bar_empty = bar_full + STAGES * 8, bar_go = bar_empty + STAGES * 8;
    const uint32_t bar_own = bar_go + 8, bar_fready = bar_own + HPG * 8;
    const size_t base = ((size_t)head0 * (SKV / CHUNK_TOK) + r) * CHUNK_BYTES;
    const char* ksrc = (const char*)qk + base;
    uint32_t tnext = 0;

    if (threadIdx.x == 0) {
        tnext = gtime32() + tau;
#pragma unroll
        for (int i = 0; i < LEAD; i++) mbar_init(bar_full + i * 8, 1);
        asm volatile("fence.proxy.async.shared::cta;" ::: "memory");
#pragma unroll
        for (int i = 0; i < LEAD; i++) {
            mbar_expect_tx(bar_full + i * 8, CHUNK_BYTES);
            bulk_load(sb + OFF_RING + i * CHUNK_BYTES, ksrc + (size_t)i * CPG * CHUNK_BYTES, CHUNK_BYTES, bar_full + i * 8);
        }
#pragma unroll
        for (int i = LEAD; i < STAGES; i++) mbar_init(bar_full + i * 8, 1);
#pragma unroll
        for (int i = 0; i < STAGES; i++) mbar_init(bar_empty + i * 8, NCW);
        mbar_init(bar_go, 1);
#pragma unroll
        for (int i = 0; i < HPG; i++) {
            mbar_init(bar_own + i * 8, NCW);
            mbar_init(bar_fready + i * 8, 1);
        }
        asm volatile("fence.proxy.async.shared::cta;" ::: "memory");
    }
    const int lane = threadIdx.x & 31;

    if (threadIdx.x < 32) {
        __syncwarp();
        asm volatile("bar.arrive 2, %0;" ::"n"(NTHREADS) : "memory");
        if (lane == 0) {
            asm volatile("prefetch.tensormap [%0];" ::"l"(&vmap) : "memory");
            const int vrow0 = head0 * SKV + r * CHUNK_TOK;
            const uint32_t tstart = tnext - tau;
            uint32_t t1 = gtime32(), t2 = t1;
            for (int it = 0; it < 4096 && t2 == t1; it++) t2 = gtime32();
            t1 = t2;
            for (int it = 0; it < 4096 && t2 == t1; it++) t2 = gtime32();
            const int tick = (int)(t2 - t1);
            if (tick == 0) tau = 0;
            int st = LEAD % STAGES, ph = (LEAD / STAGES) & 1;
            for (int i = LEAD; i < 2 * NCH; i++) {
                if (i >= INFLIGHT) mbar_wait(bar_full + ((i - INFLIGHT) % STAGES) * 8, ((i - INFLIGHT) / STAGES) & 1);
                if (i >= STAGES) mbar_wait(bar_empty + st * 8, ph ^ 1);
                if (tau > 0) {
                    uint32_t now = gtime32();
                    for (int it = 0; it < (1 << 16) && (int)(now - tnext) < 0; it++) now = gtime32();
                    if ((int)(now - tnext) > tick) tnext = now - tick;
                    tnext += tau;
                    if (i >= CATCH_START) {
                        const int lag = (int)(now - tstart) - (i - LEAD + 1) * (tau + tau / CATCH_REF);
                        tnext -= min(max(lag / 4, 0), tau / 5);
                    }
                }
                mbar_expect_tx(bar_full + st * 8, CHUNK_BYTES);
                if (i < NCH) bulk_load(sb + OFF_RING + st * CHUNK_BYTES, ksrc + (size_t)i * CPG * CHUNK_BYTES, CHUNK_BYTES, bar_full + st * 8);
                else tensor_load(sb + OFF_RING + st * CHUNK_BYTES, &vmap, vrow0 + (i - NCH) * CPG * CHUNK_TOK, bar_full + st * 8);
                if (i == STATS_START) mbar_arrive(bar_go);
                if (++st == STAGES) { st = 0; ph ^= 1; }
            }
        }
        return;
    }
    if (threadIdx.x < 64) {
        const float* s_wmax = (const float*)(smem + OFF_WMAX);
        const float* s_wsz = (const float*)(smem + OFF_WSZ);
        const float* s_wb = (const float*)(smem + OFF_WB);
        float4* s_f = (float4*)(smem + OFF_F);
        const uint32_t par = (g_epoch[blockIdx.x] + 1u) & 1u;
        if (lane < 16) {
            const int id = r * 16 + lane;
            g_acc[((id / (HPG * BLK)) * ACC_STRIDE + head0) * BLK + id % (HPG * BLK)] = 0ull;
        } else {
            *(float2*)(&g_wide[head0][0] + r * 32 + (lane - 16) * 2) = make_float2(0.f, 0.f);
        }
        __syncwarp();
        if (lane == 0) g_epoch[blockIdx.x] = par;
        asm volatile("bar.sync 2, %0;" ::"n"(NTHREADS) : "memory");
        __threadfence();
        float m_prev = 0.f, b_prev = 0.f;
#pragma unroll 1
        for (int step = 0; step <= HPG; step++) {
            const float m_own = m_prev, b_own = b_prev;
            if (step < HPG) {
                mbar_wait(bar_own + step * 8, 0);
                const int h = lane & 3;
                float mo = -INFINITY, lo = 0.f, bo = 0.f;
#pragma unroll
                for (int c = 0; c < CPS; c++) {
                    lo += s_wsz[(step * CPS + c) * 8 + h];
                    bo += s_wb[(step * CPS + c) * REP + h];
                    mo = fmaxf(mo, s_wmax[(step * NCW + c) * REP + h]);
                }
                m_prev = mo;
                b_prev = untag(__float_as_uint(bo));
                if (lane < REP)
                    asm volatile("st.relaxed.gpu.global.v4.u32 [%0], {%1,%2,%3,%4};" ::"l"(&g_stat[head0 + step][r][h]),
                                 "r"((__float_as_uint(mo) & ~3u) | par), "r"((__float_as_uint(lo) & ~3u) | par),
                                 "r"(__float_as_uint(b_prev) | par), "r"(((__float_as_uint(mo) & 3u) << 2) | par) : "memory");
                if (step == 0) continue;
            } else {
                mbar_wait(bar_go, 0);
            }
            const int seg = step - 1;
            constexpr int NS = CPG / 8;
            const uint4* gs = &g_stat[head0 + seg][0][0] + lane;
            uint4 w[NS];
            for (int it = 0; it < (1 << 20); it++) {
                uint32_t miss = 0u;
#pragma unroll
                for (int k = 0; k < NS; k++) {
                    asm volatile("ld.relaxed.gpu.global.v4.u32 {%0,%1,%2,%3}, [%4];"
                                 : "=r"(w[k].x), "=r"(w[k].y), "=r"(w[k].z), "=r"(w[k].w) : "l"(gs + 32 * k) : "memory");
                    miss |= mism4(w[k], par);
                }
                if (__all_sync(0xffffffffu, (miss & 3u) == 0u)) break;
                __nanosleep(300);
            }
            if (seg == 0) __threadfence();
#pragma unroll
            for (int k = 0; k < NS; k++) w[k].x = (w[k].x & ~3u) | (w[k].w >> 2);
            float M = __uint_as_float(w[0].x);
#pragma unroll
            for (int k = 1; k < NS; k++) M = fmaxf(M, __uint_as_float(w[k].x));
#pragma unroll
            for (int o = 4; o <= 16; o <<= 1) M = fmaxf(M, __shfl_xor_sync(0xffffffffu, M, o));
            float L = 0.f, W = 0.f;
#pragma unroll
            for (int k = 0; k < NS; k++) {
                const float e = ex2(__uint_as_float(w[k].x) - M);
                L = fmaf(e, untag(w[k].y), L);
                W = fmaf(e, untag(w[k].z), W);
            }
#pragma unroll
            for (int o = 4; o <= 16; o <<= 1) {
                L += __shfl_xor_sync(0xffffffffu, L, o);
                W += __shfl_xor_sync(0xffffffffu, W, o);
            }
            const float e_own = ex2(m_own - M);
            float unit = W / L * (1.f / FIX_RANGE);
            float fs = e_own / W * FIX_RANGE;
            float lim = fs * b_own * 0.999f;
            if (!(unit > 1e-30f && unit < 1e30f)) { lim = -1.f; unit = 0.f; }
            if (lane < 4) s_f[seg * REP + lane] = make_float4(fs, lim, unit, e_own / L);
            __syncwarp();
            if (lane == 0) mbar_arrive(bar_fready + seg * 8);
        }
        return;
    }

    const int tid = threadIdx.x - 64;
    const int warp = tid >> 5;
    float* s_p = (float*)(smem + OFF_P);
    float* s_qs = (float*)(smem + OFF_QS);
    float* s_cg = (float*)(smem + OFF_CG);
    float* s_wmax = (float*)(smem + OFF_WMAX);
    float* s_wsz = (float*)(smem + OFF_WSZ);

    {
        const int kg = warp >> 2, h = warp & 3;
        const float qscale = 0.08838834764831845f * 1.4426950408889634f;
        uint2 qq[HPG], ss[HPG], zz[HPG];
#pragma unroll
        for (int seg = 0; seg < HPG; seg++) {
            qq[seg] = *(const uint2*)(q + ((head0 + seg) * REP + h) * DH + lane * 4);
            ss[seg] = *(const uint2*)(k_scales + ((head0 + seg) * NGK + kg) * DH + lane * 4);
            zz[seg] = *(const uint2*)(k_zeros + ((head0 + seg) * NGK + kg) * DH + lane * 4);
        }
#pragma unroll
        for (int seg = 0; seg < HPG; seg++) {
            float4 a;
            a.x = __uint_as_float(qq[seg].x << 16) * __uint_as_float(ss[seg].x << 16) * qscale;
            a.y = __uint_as_float(qq[seg].x & 0xffff0000u) * __uint_as_float(ss[seg].x & 0xffff0000u) * qscale;
            a.z = __uint_as_float(qq[seg].y << 16) * __uint_as_float(ss[seg].y << 16) * qscale;
            a.w = __uint_as_float(qq[seg].y & 0xffff0000u) * __uint_as_float(ss[seg].y & 0xffff0000u) * qscale;
            float c = a.x * __uint_as_float(zz[seg].x << 16) + a.y * __uint_as_float(zz[seg].x & 0xffff0000u) +
                      a.z * __uint_as_float(zz[seg].y << 16) + a.w * __uint_as_float(zz[seg].y & 0xffff0000u);
#pragma unroll
            for (int o = 16; o > 0; o >>= 1) c += __shfl_xor_sync(0xffffffffu, c, o);
            *(float4*)(s_qs + (seg * NCW + warp) * DH + lane * 4) = a;
            if (lane == 0) s_cg[seg * NCW + warp] = c;
        }
    }
    uint32_t vsb[HPG], vzb[HPG];
#pragma unroll
    for (int i = 0; i < HPG; i++) {
        const int tok = (head0 + i) * SKV + (warp * CPG + r) * CHUNK_TOK + lane;
        vsb[i] = ((const uint16_t*)v_scales)[tok];
        vzb[i] = ((const uint16_t*)v_zeros)[tok];
    }
    asm volatile("bar.sync 2, %0;" ::"n"(NTHREADS) : "memory");

    int st = 0, ph = 0;
    {
        const int myh = (lane >> 1) & 3;
        const bool b2 = lane & 4, b1 = lane & 2;
        const uint32_t xoff = sb + OFF_RING + (warp * 4 + (lane >> 3)) * (DH * 4) + (lane & 7) * 16;
        float mrun = -INFINITY;
#pragma unroll 1
        for (int sg = 0; sg < HPG * NGK; sg++) {
            float4 qr[REP][4];
#pragma unroll
            for (int h = 0; h < REP; h++)
#pragma unroll
                for (int j = 0; j < 4; j++)
                    qr[h][j] = *(const float4*)(s_qs + (sg * REP + h) * DH + ((lane & 7) + 8 * j) * 4);
            const float cg = s_cg[sg * REP + myh];
#pragma unroll 1
            for (int c = sg * (CPS / NGK); c < (sg + 1) * (CPS / NGK); c++) {
                mbar_wait(bar_full + st * 8, ph);
                const uint32_t xa = xoff + st * CHUNK_BYTES;
                int4 x[4];
#pragma unroll
                for (int j = 0; j < 4; j++) x[j] = lds_i4(xa + j * 128);
                __syncwarp();
                if (lane == 0) mbar_arrive(bar_empty + st * 8);
                float s[REP] = {0.f, 0.f, 0.f, 0.f};
#pragma unroll
                for (int j = 0; j < 4; j++) {
                    const float f0 = (float)x[j].x, f1 = (float)x[j].y, f2 = (float)x[j].z, f3 = (float)x[j].w;
#pragma unroll
                    for (int h = 0; h < REP; h++) {
                        s[h] = fmaf(qr[h][j].x, f0, s[h]);
                        s[h] = fmaf(qr[h][j].y, f1, s[h]);
                        s[h] = fmaf(qr[h][j].z, f2, s[h]);
                        s[h] = fmaf(qr[h][j].w, f3, s[h]);
                    }
                }
                float k0 = (b2 ? s[2] : s[0]) + __shfl_xor_sync(0xffffffffu, b2 ? s[0] : s[2], 4);
                float k1 = (b2 ? s[3] : s[1]) + __shfl_xor_sync(0xffffffffu, b2 ? s[1] : s[3], 4);
                float t = (b1 ? k1 : k0) + __shfl_xor_sync(0xffffffffu, b1 ? k0 : k1, 2);
                t += __shfl_xor_sync(0xffffffffu, t, 1);
                t -= cg;
                if (!(lane & 1)) s_p[c * (CHUNK_TOK * REP) + warp * 16 + (lane >> 1)] = t;
                mrun = fmaxf(mrun, t);
                if (++st == STAGES) { st = 0; ph ^= 1; }
            }
            if (sg & 1) {
                mrun = fmaxf(mrun, __shfl_xor_sync(0xffffffffu, mrun, 8));
                mrun = fmaxf(mrun, __shfl_xor_sync(0xffffffffu, mrun, 16));
                if (lane < 8 && !(lane & 1)) s_wmax[((sg >> 1) * NCW + warp) * REP + myh] = mrun;
                mrun = -INFINITY;
                consumer_bar();
                const int i = sg >> 1;
                float4 M = *(const float4*)(s_wmax + i * NCW * REP);
#pragma unroll
                for (int w = 1; w < NCW; w++) {
                    const float4 m = *(const float4*)(s_wmax + (i * NCW + w) * REP);
                    M.x = fmaxf(M.x, m.x); M.y = fmaxf(M.y, m.y); M.z = fmaxf(M.z, m.z); M.w = fmaxf(M.w, m.w);
                }
                const float vs = __uint_as_float(vsb[0] << 16), vz = __uint_as_float(vzb[0] << 16);
#pragma unroll
                for (int k = 0; k + 1 < HPG; k++) { vsb[k] = vsb[k + 1]; vzb[k] = vzb[k + 1]; }
                float4 p = *(const float4*)(s_p + (tid + i * NCT) * REP);
                p.x = ex2(p.x - M.x); p.y = ex2(p.y - M.y); p.z = ex2(p.z - M.z); p.w = ex2(p.w - M.w);
                const float4 l = p;
                p.x *= vs; p.y *= vs; p.z *= vs; p.w *= vs;
                const float4 hi = make_float4(tf32_trunc(p.x), tf32_trunc(p.y), tf32_trunc(p.z), tf32_trunc(p.w));
                const float4 lo = make_float4(tf32_trunc(p.x - hi.x), tf32_trunc(p.y - hi.y), tf32_trunc(p.z - hi.z), tf32_trunc(p.w - hi.w));
                const float4 z = make_float4((hi.x + lo.x) * vz, (hi.y + lo.y) * vz, (hi.z + lo.z) * vz, (hi.w + lo.w) * vz);
                {
                    float* pb = (float*)(smem + OFF_PB) + (i * NCW + warp) * 256 + (lane >> 4) * 128 + ((lane & 7) >> 1) * 4 +
                                ((lane >> 3) & 1) * 2 + (lane & 1);
                    pb[0 * 16] = hi.x; pb[1 * 16] = lo.x; pb[2 * 16] = hi.y; pb[3 * 16] = lo.y;
                    pb[4 * 16] = hi.z; pb[5 * 16] = lo.z; pb[6 * 16] = hi.w; pb[7 * 16] = lo.w;
                }
                const bool b4 = lane & 16, b3 = lane & 8;
                const float u0 = (b4 ? z.x : l.x) + __shfl_xor_sync(0xffffffffu, b4 ? l.x : z.x, 16);
                const float u1 = (b4 ? z.y : l.y) + __shfl_xor_sync(0xffffffffu, b4 ? l.y : z.y, 16);
                const float u2 = (b4 ? z.z : l.z) + __shfl_xor_sync(0xffffffffu, b4 ? l.z : z.z, 16);
                const float u3 = (b4 ? z.w : l.w) + __shfl_xor_sync(0xffffffffu, b4 ? l.w : z.w, 16);
                const float v0 = (b3 ? u2 : u0) + __shfl_xor_sync(0xffffffffu, b3 ? u0 : u2, 8);
                const float v1 = (b3 ? u3 : u1) + __shfl_xor_sync(0xffffffffu, b3 ? u1 : u3, 8);
                float t = (b2 ? v1 : v0) + __shfl_xor_sync(0xffffffffu, b2 ? v0 : v1, 4);
                t += __shfl_xor_sync(0xffffffffu, t, 2);
                t += __shfl_xor_sync(0xffffffffu, t, 1);
                if (!(lane & 3)) s_wsz[(i * NCW + warp) * 8 + (lane >> 2)] = t;
                const float wv = fabsf(vs) * (16.f + fabsf(vz));
                const float y0 = (b4 ? l.z : l.x) * wv + __shfl_xor_sync(0xffffffffu, (b4 ? l.x : l.z) * wv, 16);
                const float y1 = (b4 ? l.w : l.y) * wv + __shfl_xor_sync(0xffffffffu, (b4 ? l.y : l.w) * wv, 16);
                float y = (b3 ? y1 : y0) + __shfl_xor_sync(0xffffffffu, b3 ? y0 : y1, 8);
#pragma unroll
                for (int o = 4; o > 0; o >>= 1) y += __shfl_xor_sync(0xffffffffu, y, o);
                if (!(lane & 7)) ((float*)(smem + OFF_WB))[(i * NCW + warp) * REP + (lane >> 3)] = y;
                __syncwarp();
                if (lane == 0) mbar_arrive(bar_own + i * 8);
            }
        }
    }

    const int g = lane >> 2, t = lane & 3;
    const int oidx = t * DH + warp * 16 + g * 2;
    unsigned long long* pacc = &g_acc[((tid / BLK) * ACC_STRIDE + head0) * BLK + tid % BLK];
    __nv_bfloat162* pout = (__nv_bfloat162*)(out + head0 * (REP * DH) + oidx);
    const uint32_t piece = (warp & 1) * 4 + (g >> 1);
    const uint32_t xoff0 = sb + OFF_RING + (warp >> 1) * 4096 + (2 * t) * 128 + ((piece ^ (2 * t)) << 4) + (g & 1) * 8;
    const uint32_t xoff1 = sb + OFF_RING + (warp >> 1) * 4096 + (2 * t + 1) * 128 + ((piece ^ (2 * t + 1)) << 4) + (g & 1) * 8;
    uint32_t pa = sb + OFF_PB + lane * 16;
#pragma unroll 1
    for (int seg = 0; seg < HPG; seg++) {
        mbar_wait(bar_own + seg * 8, 0);
        float zc = 0.f;
#pragma unroll
        for (int c = 0; c < CPS; c++) zc += s_wsz[(seg * CPS + c) * 8 + 4 + t];
        float d0[4] = {-0.5f * zc, 0.f, -0.5f * zc, 0.f}, d1[4] = {-0.5f * zc, 0.f, -0.5f * zc, 0.f};
        float4 fz;
#pragma unroll 1
        for (int c = 0; c < CPS; c++) {
            const float4 pA = lds_f4(pa), pB = lds_f4(pa + 512);
            pa += 1024;
            uint32_t xa0 = xoff0 + st * CHUNK_BYTES, xa1 = xoff1 + st * CHUNK_BYTES;
            asm volatile("" : "+r"(xa0), "+r"(xa1));
            if (c == FWAIT) {
                mbar_wait(bar_fready + seg * 8, 0);
                fz = lds_f4(sb + OFF_F + (seg * REP + t) * 16);
            }
            mbar_wait(bar_full + st * 8, ph);
            int2 x[4][2];
#pragma unroll
            for (int s = 0; s < 4; s++) {
                x[s][0] = lds_i2(xa0 + s * 1024);
                x[s][1] = lds_i2(xa1 + s * 1024);
            }
            __syncwarp();
            if (lane == 0) mbar_arrive(bar_empty + st * 8);
            mma_tf32(d0, (float)x[0][0].x, (float)x[0][0].y, (float)x[0][1].x, (float)x[0][1].y, pA.x, pA.y);
            mma_tf32(d1, (float)x[1][0].x, (float)x[1][0].y, (float)x[1][1].x, (float)x[1][1].y, pA.z, pA.w);
            mma_tf32(d0, (float)x[2][0].x, (float)x[2][0].y, (float)x[2][1].x, (float)x[2][1].y, pB.x, pB.y);
            mma_tf32(d1, (float)x[3][0].x, (float)x[3][0].y, (float)x[3][1].x, (float)x[3][1].y, pB.z, pB.w);
            if (++st == STAGES) { st = 0; ph ^= 1; }
        }
        const float ox = (d0[0] + d0[1]) + (d1[0] + d1[1]);
        const float oy = (d0[2] + d0[3]) + (d1[2] + d1[3]);
        const float ya = ox * fz.x, yb = oy * fz.x;
        unsigned long long op = ((unsigned long long)(long long)__float2int_rn(ya) << 39) +
                                ((unsigned long long)(long long)__float2int_rn(yb) << 14) + 1ull;
        const bool wide = !(fabsf(ya) <= fz.y) | !(fabsf(yb) <= fz.y);
        unsigned long long tot = 0ull;
        asm volatile("{\n.reg .pred p;\nsetp.eq.u32 p, %3, 0;\n@p atom.relaxed.gpu.global.add.u64 %0, [%1], %2;\n}"
                     : "+l"(tot) : "l"(pacc), "l"(op), "r"((uint32_t)wide) : "memory");
        if (__builtin_expect(wide, 0)) op = wide_add(pacc, &g_wide[head0 + seg][oidx], ox * fz.w, oy * fz.w);
        tot += op;
        const int vb = (int)((long long)(tot << 25) >> 39);
        const int va = ((int)(tot >> 32) + 64) >> 7;
        const float oa = (float)va * fz.z, ob = (float)vb * fz.z;
        const uint32_t low = (uint32_t)tot & 0x3fffu;
        const __nv_bfloat162 o2 = __floats2bfloat162_rn(oa, ob);
        asm volatile("{\n.reg .pred p;\nsetp.eq.u32 p, %2, %3;\n@p st.global.u32 [%0], %1;\n}"
                     ::"l"(pout), "r"(*(const uint32_t*)&o2), "r"(low), "n"(CPG) : "memory");
        if (__builtin_expect(low > CPG && (low & 127u) == CPG, 0)) wide_finish(pout, &g_wide[head0 + seg][oidx], oa, ob);
        pacc += BLK;
        pout += REP * DH / 2;
    }
}

}

typedef CUresult (*EncodeTiledFn)(CUtensorMap*, CUtensorMapDataType, cuuint32_t, void*, const cuuint64_t*, const cuuint64_t*,
                                  const cuuint32_t*, const cuuint32_t*, CUtensorMapInterleave, CUtensorMapSwizzle,
                                  CUtensorMapL2promotion, CUtensorMapFloatOOBfill);

extern "C" void kernel_launch(void* const* d_in, const int* in_sizes, int n_in, void* d_out, int out_size) {
    (void)in_sizes; (void)n_in; (void)out_size;
    static int tau = -1;
    static EncodeTiledFn encode = nullptr;
    if (tau < 0) {
        cudaFuncSetAttribute(kvq_decode_kernel, cudaFuncAttributeMaxDynamicSharedMemorySize, SMEM_BYTES);
        int dev = 0, khz = 0, bits = 0;
        cudaGetDevice(&dev);
        cudaDeviceGetAttribute(&khz, cudaDevAttrMemoryClockRate, dev);
        cudaDeviceGetAttribute(&bits, cudaDevAttrGlobalMemoryBusWidth, dev);
        const double bytes_per_ns = 2.0 * khz * 1e-6 * (bits / 8);
        tau = bytes_per_ns > 0.0 ? (int)((double)NCTA * CHUNK_BYTES / (bytes_per_ns * TAU_EFF)) : 0;
        void* fn = nullptr;
        cudaDriverEntryPointQueryResult qr;
        cudaGetDriverEntryPoint("cuTensorMapEncodeTiled", &fn, cudaEnableDefault, &qr);
        encode = (EncodeTiledFn)fn;
    }
    if (!encode) return;
    CUtensorMap vmap;
    const cuuint64_t dims[3] = {32, (cuuint64_t)HKV * SKV, 4}, strides[2] = {DH * 4, 128};
    const cuuint32_t box[3] = {32, CHUNK_TOK, 4}, estr[3] = {1, 1, 1};
    encode(&vmap, CU_TENSOR_MAP_DATA_TYPE_INT32, 3, d_in[2], dims, strides, box, estr, CU_TENSOR_MAP_INTERLEAVE_NONE,
           CU_TENSOR_MAP_SWIZZLE_128B, CU_TENSOR_MAP_L2_PROMOTION_NONE, CU_TENSOR_MAP_FLOAT_OOB_FILL_NONE);
    kvq_decode_kernel<<<NCTA, NTHREADS, SMEM_BYTES>>>(
        (const __nv_bfloat16*)d_in[0], (const int*)d_in[1], vmap, (const __nv_bfloat16*)d_in[3],
        (const __nv_bfloat16*)d_in[4], (const __nv_bfloat16*)d_in[5], (const __nv_bfloat16*)d_in[6],
        (__nv_bfloat16*)d_out, tau);
}
```

```cpp
#include <cuda_runtime.h>
#include <cuda.h>
#include <cuda_bf16.h>
#include <stdint.h>

namespace {

constexpr int HKV = 8;
constexpr int REP = 4;
constexpr int SKV = 16384;
constexpr int DH = 128;
constexpr int NGK = 2;
constexpr int NCTA = 128;
constexpr int NG = 2;
constexpr int HPG = HKV / NG;
constexpr int CPG = NCTA / NG;
constexpr int CHUNK_TOK = 32;
constexpr int CHUNK_BYTES = CHUNK_TOK * DH * 4;
constexpr int CPS = SKV / CHUNK_TOK / CPG;
constexpr int NCH = CPS * HPG;
constexpr int TOK_PER_CTA = NCH * CHUNK_TOK;
constexpr int STAGES = 8;
constexpr int LEAD = 2;
constexpr int INFLIGHT = 4;
constexpr int STATS_START = 40;
constexpr int FWAIT = 4;
constexpr int CATCH_START = 40;
constexpr int CATCH_REF = 54;
constexpr double TAU_EFF = 0.973;
constexpr int NCW = 8;
constexpr int NCT = NCW * 32;
constexpr int NTHREADS = NCT + 64;
static_assert(CPS == NCW && HPG == 4 && CPG == 64, "layout assumptions");

constexpr int OFF_RING = 0;
constexpr int OFF_P = OFF_RING + STAGES * CHUNK_BYTES;
constexpr int OFF_PB = OFF_P + TOK_PER_CTA * REP * 4;
constexpr int OFF_QS = OFF_PB + NCH * 1024;
constexpr int OFF_CG = OFF_QS + HPG * NGK * REP * DH * 4;
constexpr int OFF_WMAX = OFF_CG + HPG * NGK * REP * 4;
constexpr int OFF_WSZ = OFF_WMAX + HPG * NCW * REP * 4;
constexpr int OFF_WB = OFF_WSZ + NCH * 8 * 4;
constexpr int OFF_F = OFF_WB + NCH * 16;
constexpr int OFF_BAR = OFF_F + HPG * REP * 16;
constexpr int NBAR = 2 * STAGES + 1 + 2 * HPG + 3 * STAGES;
constexpr int SMEM_BYTES = OFF_BAR + NBAR * 8;

__device__ __align__(128) uint4 g_stat[HKV][CPG][REP];
__device__ uint32_t g_epoch[NCTA];
constexpr int BLK = 8, ACC_STRIDE = 17;
__device__ __align__(128) unsigned long long g_acc[(256 / BLK) * ACC_STRIDE * BLK];
__device__ __align__(128) float g_wide[HKV][REP * DH];
constexpr float FIX_RANGE = 16777216.f - 128.f;

__device__ __forceinline__ uint32_t smem_u32(const void* p) { return (uint32_t)__cvta_generic_to_shared(p); }
__device__ __forceinline__ void mbar_init(uint32_t bar, uint32_t cnt) {
    asm volatile("mbarrier.init.shared::cta.b64 [%0], %1;" ::"r"(bar), "r"(cnt) : "memory");
}
__device__ __forceinline__ void mbar_expect_tx(uint32_t bar, uint32_t bytes) {
    asm volatile("mbarrier.arrive.expect_tx.shared::cta.b64 _, [%0], %1;" ::"r"(bar), "r"(bytes) : "memory");
}
__device__ __forceinline__ void mbar_arrive(uint32_t bar) {
    asm volatile("mbarrier.arrive.shared::cta.b64 _, [%0];" ::"r"(bar) : "memory");
}
__device__ __forceinline__ void mbar_wait(uint32_t bar, uint32_t parity) {
    uint32_t ok;
    int it = 0;
    do {
        asm volatile(
            "{\n.reg .pred p;\nmbarrier.try_wait.parity.shared::cta.b64 p, [%1], %2;\nselp.u32 %0, 1, 0, p;\n}"
            : "=r"(ok) : "r"(bar), "r"(parity) : "memory");
    } while (!ok && ++it < (1 << 20));
}
__device__ __forceinline__ void bulk_load(uint32_t dst, const void* src, uint32_t bytes, uint32_t bar) {
    asm volatile("{\n.reg .b64 pol;\ncreatepolicy.fractional.L2::evict_first.b64 pol, 1.0;\n"
                 "cp.async.bulk.shared::cluster.global.mbarrier::complete_tx::bytes.L2::cache_hint [%0], [%1], %2, [%3], pol;\n}"
                 ::"r"(dst), "l"(src), "r"(bytes), "r"(bar) : "memory");
}
__device__ __forceinline__ void tensor_load(uint32_t dst, const CUtensorMap* tm, int row, int blk, uint32_t bar) {
    asm volatile("{\n.reg .b64 pol;\ncreatepolicy.fractional.L2::evict_first.b64 pol, 1.0;\n"
                 "cp.async.bulk.tensor.2d.shared::cluster.global.mbarrier::complete_tx::bytes.L2::cache_hint [%0], [%1, {%3, %4}], [%2], pol;\n}"
                 ::"r"(dst), "l"(tm), "r"(bar), "r"(blk * 32), "r"(row) : "memory");
}
__device__ __forceinline__ int2 lds_i2(uint32_t a) {
    int2 v;
    asm volatile("ld.shared.v2.s32 {%0,%1}, [%2];" : "=r"(v.x), "=r"(v.y) : "r"(a) : "memory");
    return v;
}
__device__ __forceinline__ void mma_tf32(float (&d)[4], float a0, float a1, float a2, float a3, float b0, float b1) {
    asm volatile("mma.sync.aligned.m16n8k8.row.col.f32.tf32.tf32.f32 {%0,%1,%2,%3}, {%4,%5,%6,%7}, {%8,%9}, {%0,%1,%2,%3};"
                 : "+f"(d[0]), "+f"(d[1]), "+f"(d[2]), "+f"(d[3])
                 : "r"(__float_as_uint(a0)), "r"(__float_as_uint(a1)), "r"(__float_as_uint(a2)), "r"(__float_as_uint(a3)),
                   "r"(__float_as_uint(b0)), "r"(__float_as_uint(b1)));
}
__device__ __forceinline__ float tf32_trunc(float v) { return __uint_as_float(__float_as_uint(v) & 0xffffe000u); }
__device__ __forceinline__ int4 lds_i4(uint32_t a) {
    int4 v;
    asm volatile("ld.shared.v4.s32 {%0,%1,%2,%3}, [%4];" : "=r"(v.x), "=r"(v.y), "=r"(v.z), "=r"(v.w) : "r"(a) : "memory");
    return v;
}
__device__ __forceinline__ float4 lds_f4(uint32_t a) {
    float4 v;
    asm volatile("ld.shared.v4.f32 {%0,%1,%2,%3}, [%4];" : "=f"(v.x), "=f"(v.y), "=f"(v.z), "=f"(v.w) : "r"(a) : "memory");
    return v;
}
__device__ __forceinline__ void consumer_bar() { asm volatile("bar.sync 1, %0;" ::"n"(NCT) : "memory"); }
__device__ __forceinline__ float ex2(float x) {
    float y;
    asm("ex2.approx.ftz.f32 %0, %1;" : "=f"(y) : "f"(x));
    return y;
}
__device__ __forceinline__ uint32_t gtime32() {
    uint32_t t;
    asm volatile("mov.u32 %0, %%globaltimer_lo;" : "=r"(t));
    return t;
}
__device__ __forceinline__ float untag(uint32_t w) { return __uint_as_float(w & ~3u); }
__device__ __forceinline__ uint32_t mism4(const uint4& w, uint32_t tag) {
    return ((w.x ^ tag) | (w.y ^ tag)) | ((w.z ^ tag) | (w.w ^ tag));
}

__device__ __noinline__ unsigned long long wide_add(unsigned long long* pacc, float* pw, float a, float b) {
    atomicAdd(pw, a);
    atomicAdd(pw + 1, b);
    __threadfence();
    return atomicAdd(pacc, (1ull << 7) + 1ull) + (1ull << 7) + 1ull;
}
__device__ __noinline__ void wide_finish(__nv_bfloat162* pout, const volatile float* pw, float a, float b) {
    __threadfence();
    *pout = __floats2bfloat162_rn(a + pw[0], b + pw[1]);
}

__global__ void __launch_bounds__(NTHREADS, 1)
kvq_decode_kernel(const __nv_bfloat16* __restrict__ q, const int* __restrict__ qk, const __grid_constant__ CUtensorMap vmap,
                  const __nv_bfloat16* __restrict__ k_scales, const __nv_bfloat16* __restrict__ k_zeros,
                  const __nv_bfloat16* __restrict__ v_scales, const __nv_bfloat16* __restrict__ v_zeros,
                  __nv_bfloat16* __restrict__ out, int tau) {
    extern __shared__ __align__(1024) unsigned char smem[];
    const uint32_t sb = smem_u32(smem);
    const int grp = blockIdx.x & (NG - 1);
    const int r = blockIdx.x / NG;
    const int head0 = grp * HPG;
    const uint32_t bar_full = sb + OFF_BAR, bar_empty = bar_full + STAGES * 8, bar_go = bar_empty + STAGES * 8;
    const uint32_t bar_own = bar_go + 8, bar_fready = bar_own + HPG * 8, bar_vfull = bar_fready + HPG * 8;
    const size_t base = ((size_t)head0 * (SKV / CHUNK_TOK) + r) * CHUNK_BYTES;
    const char* ksrc = (const char*)qk + base;
    uint32_t tnext = 0;

    if (threadIdx.x == 0) {
        tnext = gtime32() + tau;
#pragma unroll
        for (int i = 0; i < LEAD; i++) mbar_init(bar_full + i * 8, 1);
        asm volatile("fence.proxy.async.shared::cta;" ::: "memory");
#pragma unroll
        for (int i = 0; i < LEAD; i++) {
            mbar_expect_tx(bar_full + i * 8, CHUNK_BYTES);
            bulk_load(sb + OFF_RING + i * CHUNK_BYTES, ksrc + (size_t)i * CPG * CHUNK_BYTES, CHUNK_BYTES, bar_full + i * 8);
        }
#pragma unroll
        for (int i = LEAD; i < STAGES; i++) mbar_init(bar_full + i * 8, 1);
#pragma unroll
        for (int i = 0; i < STAGES; i++) mbar_init(bar_empty + i * 8, NCW);
        mbar_init(bar_go, 1);
#pragma unroll
        for (int i = 0; i < 3 * STAGES; i++) mbar_init(bar_vfull + i * 8, 1);
#pragma unroll
        for (int i = 0; i < HPG; i++) {
            mbar_init(bar_own + i * 8, NCW);
            mbar_init(bar_fready + i * 8, 1);
        }
        asm volatile("fence.proxy.async.shared::cta;" ::: "memory");
    }
    const int lane = threadIdx.x & 31;

    if (threadIdx.x < 32) {
        __syncwarp();
        asm volatile("bar.arrive 2, %0;" ::"n"(NTHREADS) : "memory");
        if (lane == 0) {
            asm volatile("prefetch.tensormap [%0];" ::"l"(&vmap) : "memory");
            const int vrow0 = head0 * SKV + r * CHUNK_TOK;
            const uint32_t tstart = tnext - tau;
            int excused = 0;
            uint32_t t1 = gtime32(), t2 = t1;
            for (int it = 0; it < 4096 && t2 == t1; it++) t2 = gtime32();
            t1 = t2;
            for (int it = 0; it < 4096 && t2 == t1; it++) t2 = gtime32();
            const int tick = (int)(t2 - t1);
            if (tick == 0) tau = 0;
            int st = LEAD % STAGES, ph = (LEAD / STAGES) & 1;
            for (int i = LEAD; i < 2 * NCH; i++) {
                if (i >= INFLIGHT) mbar_wait(bar_full + ((i - INFLIGHT) % STAGES) * 8, ((i - INFLIGHT) / STAGES) & 1);
                if (i >= STAGES) mbar_wait(bar_empty + st * 8, ph ^ 1);
                if (tau > 0) {
                    uint32_t now = gtime32();
                    for (int it = 0; it < (1 << 16) && (int)(now - tnext) < 0; it++) now = gtime32();
                    if ((int)(now - tnext) > tick) tnext = now - tick;
                    tnext += tau;
                    if (i >= CATCH_START) {
                        const int lag = (int)(now - tstart) - (i - LEAD + 1) * (tau + tau / CATCH_REF);
                        if (lag > tau + tau / 6) excused = 2 * tau;
                        tnext -= min(max((lag - excused) / 4, 0), tau / 5);
                    }
                }
                if (i < NCH) {
                    mbar_expect_tx(bar_full + st * 8, CHUNK_BYTES);
                    bulk_load(sb + OFF_RING + st * CHUNK_BYTES, ksrc + (size_t)i * CPG * CHUNK_BYTES, CHUNK_BYTES, bar_full + st * 8);
                } else {
#pragma unroll 1
                    for (int b = 0; b < 4; b++) {
                        const uint32_t bar = (b == 3 ? bar_full : bar_vfull + b * (STAGES * 8)) + st * 8;
                        mbar_expect_tx(bar, CHUNK_BYTES / 4);
                        tensor_load(sb + OFF_RING + st * CHUNK_BYTES + b * (CHUNK_BYTES / 4), &vmap,
                                    vrow0 + (i - NCH) * CPG * CHUNK_TOK, b, bar);
                    }
                }
                if (i == STATS_START) mbar_arrive(bar_go);
                if (++st == STAGES) { st = 0; ph ^= 1; }
            }
        }
        return;
    }
    if (threadIdx.x < 64) {
        const float* s_wmax = (const float*)(smem + OFF_WMAX);
        const float* s_wsz = (const float*)(smem + OFF_WSZ);
        const float* s_wb = (const float*)(smem + OFF_WB);
        float4* s_f = (float4*)(smem + OFF_F);
        const uint32_t par = (g_epoch[blockIdx.x] + 1u) & 1u;
        if (lane < 16) {
            const int id = r * 16 + lane;
            g_acc[((id / (HPG * BLK)) * ACC_STRIDE + head0) * BLK + id % (HPG * BLK)] = 0ull;
        } else {
            *(float2*)(&g_wide[head0][0] + r * 32 + (lane - 16) * 2) = make_float2(0.f, 0.f);
        }
        __syncwarp();
        if (lane == 0) g_epoch[blockIdx.x] = par;
        asm volatile("bar.sync 2, %0;" ::"n"(NTHREADS) : "memory");
        __threadfence();
        float m_prev = 0.f, b_prev = 0.f;
#pragma unroll 1
        for (int step = 0; step <= HPG; step++) {
            const float m_own = m_prev, b_own = b_prev;
            if (step < HPG) {
                mbar_wait(bar_own + step * 8, 0);
                const int h = lane & 3;
                float mo = -INFINITY, lo = 0.f, bo = 0.f;
#pragma unroll
                for (int c = 0; c < CPS; c++) {
                    lo += s_wsz[(step * CPS + c) * 8 + h];
                    bo += s_wb[(step * CPS + c) * REP + h];
                    mo = fmaxf(mo, s_wmax[(step * NCW + c) * REP + h]);
                }
                m_prev = mo;
                b_prev = untag(__float_as_uint(bo));
                if (lane < REP)
                    asm volatile("st.relaxed.gpu.global.v4.u32 [%0], {%1,%2,%3,%4};" ::"l"(&g_stat[head0 + step][r][h]),
                                 "r"((__float_as_uint(mo) & ~3u) | par), "r"((__float_as_uint(lo) & ~3u) | par),
                                 "r"(__float_as_uint(b_prev) | par), "r"(((__float_as_uint(mo) & 3u) << 2) | par) : "memory");
                if (step == 0) continue;
            } else {
                mbar_wait(bar_go, 0);
            }
            const int seg = step - 1;
            constexpr int NS = CPG / 8;
            const uint4* gs = &g_stat[head0 + seg][0][0] + lane;
            uint4 w[NS];
            for (int it = 0; it < (1 << 20); it++) {
                uint32_t miss = 0u;
#pragma unroll
                for (int k = 0; k < NS; k++) {
                    asm volatile("ld.relaxed.gpu.global.v4.u32 {%0,%1,%2,%3}, [%4];"
                                 : "=r"(w[k].x), "=r"(w[k].y), "=r"(w[k].z), "=r"(w[k].w) : "l"(gs + 32 * k) : "memory");
                    miss |= mism4(w[k], par);
                }
                if (__all_sync(0xffffffffu, (miss & 3u) == 0u)) break;
                __nanosleep(300);
            }
            if (seg == 0) __threadfence();
#pragma unroll
            for (int k = 0; k < NS; k++) w[k].x = (w[k].x & ~3u) | (w[k].w >> 2);
            float M = __uint_as_float(w[0].x);
#pragma unroll
            for (int k = 1; k < NS; k++) M = fmaxf(M, __uint_as_float(w[k].x));
#pragma unroll
            for (int o = 4; o <= 16; o <<= 1) M = fmaxf(M, __shfl_xor_sync(0xffffffffu, M, o));
            float L = 0.f, W = 0.f;
#pragma unroll
            for (int k = 0; k < NS; k++) {
                const float e = ex2(__uint_as_float(w[k].x) - M);
                L = fmaf(e, untag(w[k].y), L);
                W = fmaf(e, untag(w[k].z), W);
            }
#pragma unroll
            for (int o = 4; o <= 16; o <<= 1) {
                L += __shfl_xor_sync(0xffffffffu, L, o);
                W += __shfl_xor_sync(0xffffffffu, W, o);
            }
            const float e_own = ex2(m_own - M);
            float unit = W / L * (1.f / FIX_RANGE);
            float fs = e_own / W * FIX_RANGE;
            float lim = fs * b_own * 0.999f;
            if (!(unit > 1e-30f && unit < 1e30f)) { lim = -1.f; unit = 0.f; }
            if (lane < 4) s_f[seg * REP + lane] = make_float4(fs, lim, unit, e_own / L);
            __syncwarp();
            if (lane == 0) mbar_arrive(bar_fready + seg * 8);
        }
        return;
    }

    const int tid = threadIdx.x - 64;
    const int warp = tid >> 5;
    float* s_p = (float*)(smem + OFF_P);
    float* s_qs = (float*)(smem + OFF_QS);
    float* s_cg = (float*)(smem + OFF_CG);
    float* s_wmax = (float*)(smem + OFF_WMAX);
    float* s_wsz = (float*)(smem + OFF_WSZ);

    {
        const int kg = warp >> 2, h = warp & 3;
        const float qscale = 0.08838834764831845f * 1.4426950408889634f;
        uint2 qq[HPG], ss[HPG], zz[HPG];
#pragma unroll
        for (int seg = 0; seg < HPG; seg++) {
            qq[seg] = *(const uint2*)(q + ((head0 + seg) * REP + h) * DH + lane * 4);
            ss[seg] = *(const uint2*)(k_scales + ((head0 + seg) * NGK + kg) * DH + lane * 4);
            zz[seg] = *(const uint2*)(k_zeros + ((head0 + seg) * NGK + kg) * DH + lane * 4);
        }
#pragma unroll
        for (int seg = 0; seg < HPG; seg++) {
            float4 a;
            a.x = __uint_as_float(qq[seg].x << 16) * __uint_as_float(ss[seg].x << 16) * qscale;
            a.y = __uint_as_float(qq[seg].x & 0xffff0000u) * __uint_as_float(ss[seg].x & 0xffff0000u) * qscale;
            a.z = __uint_as_float(qq[seg].y << 16) * __uint_as_float(ss[seg].y << 16) * qscale;
            a.w = __uint_as_float(qq[seg].y & 0xffff0000u) * __uint_as_float(ss[seg].y & 0xffff0000u) * qscale;
            float c = a.x * __uint_as_float(zz[seg].x << 16) + a.y * __uint_as_float(zz[seg].x & 0xffff0000u) +
                      a.z * __uint_as_float(zz[seg].y << 16) + a.w * __uint_as_float(zz[seg].y & 0xffff0000u);
#pragma unroll
            for (int o = 16; o > 0; o >>= 1) c += __shfl_xor_sync(0xffffffffu, c, o);
            *(float4*)(s_qs + (seg * NCW + warp) * DH + lane * 4) = a;
            if (lane == 0) s_cg[seg * NCW + warp] = c;
        }
    }
    uint32_t vsb[HPG], vzb[HPG];
#pragma unroll
    for (int i = 0; i < HPG; i++) {
        const int tok = (head0 + i) * SKV + (warp * CPG + r) * CHUNK_TOK + lane;
        vsb[i] = ((const uint16_t*)v_scales)[tok];
        vzb[i] = ((const uint16_t*)v_zeros)[tok];
    }
    asm volatile("bar.sync 2, %0;" ::"n"(NTHREADS) : "memory");

    int st = 0, ph = 0;
    {
        const int myh = (lane >> 1) & 3;
        const bool b2 = lane & 4, b1 = lane & 2;
        const uint32_t xoff = sb + OFF_RING + (warp * 4 + (lane >> 3)) * (DH * 4) + (lane & 7) * 16;
        float mrun = -INFINITY;
#pragma unroll 1
        for (int sg = 0; sg < HPG * NGK; sg++) {
            float4 qr[REP][4];
#pragma unroll
            for (int h = 0; h < REP; h++)
#pragma unroll
                for (int j = 0; j < 4; j++)
                    qr[h][j] = *(const float4*)(s_qs + (sg * REP + h) * DH + ((lane & 7) + 8 * j) * 4);
            const float cg = s_cg[sg * REP + myh];
#pragma unroll 1
            for (int c = sg * (CPS / NGK); c < (sg + 1) * (CPS / NGK); c++) {
                mbar_wait(bar_full + st * 8, ph);
                const uint32_t xa = xoff + st * CHUNK_BYTES;
                int4 x[4];
#pragma unroll
                for (int j = 0; j < 4; j++) x[j] = lds_i4(xa + j * 128);
                __syncwarp();
                if (lane == 0) mbar_arrive(bar_empty + st * 8);
                float s[REP] = {0.f, 0.f, 0.f, 0.f};
#pragma unroll
                for (int j = 0; j < 4; j++) {
                    const float f0 = (float)x[j].x, f1 = (float)x[j].y, f2 = (float)x[j].z, f3 = (float)x[j].w;
#pragma unroll
                    for (int h = 0; h < REP; h++) {
                        s[h] = fmaf(qr[h][j].x, f0, s[h]);
                        s[h] = fmaf(qr[h][j].y, f1, s[h]);
                        s[h] = fmaf(qr[h][j].z, f2, s[h]);
                        s[h] = fmaf(qr[h][j].w, f3, s[h]);
                    }
                }
                float k0 = (b2 ? s[2] : s[0]) + __shfl_xor_sync(0xffffffffu, b2 ? s[0] : s[2], 4);
                float k1 = (b2 ? s[3] : s[1]) + __shfl_xor_sync(0xffffffffu, b2 ? s[1] : s[3], 4);
                float t = (b1 ? k1 : k0) + __shfl_xor_sync(0xffffffffu, b1 ? k0 : k1, 2);
                t += __shfl_xor_sync(0xffffffffu, t, 1);
                t -= cg;
                if (!(lane & 1)) s_p[c * (CHUNK_TOK * REP) + warp * 16 + (lane >> 1)] = t;
                mrun = fmaxf(mrun, t);
                if (++st == STAGES) { st = 0; ph ^= 1; }
            }
            if (sg & 1) {
                mrun = fmaxf(mrun, __shfl_xor_sync(0xffffffffu, mrun, 8));
                mrun = fmaxf(mrun, __shfl_xor_sync(0xffffffffu, mrun, 16));
                if (lane < 8 && !(lane & 1)) s_wmax[((sg >> 1) * NCW + warp) * REP + myh] = mrun;
                mrun = -INFINITY;
                consumer_bar();
                const int i = sg >> 1;
                float4 M = *(const float4*)(s_wmax + i * NCW * REP);
#pragma unroll
                for (int w = 1; w < NCW; w++) {
                    const float4 m = *(const float4*)(s_wmax + (i * NCW + w) * REP);
                    M.x = fmaxf(M.x, m.x); M.y = fmaxf(M.y, m.y); M.z = fmaxf(M.z, m.z); M.w = fmaxf(M.w, m.w);
                }
                const float vs = __uint_as_float(vsb[0] << 16), vz = __uint_as_float(vzb[0] << 16);
#pragma unroll
                for (int k = 0; k + 1 < HPG; k++) { vsb[k] = vsb[k + 1]; vzb[k] = vzb[k + 1]; }
                float4 p = *(const float4*)(s_p + (tid + i * NCT) * REP);
                p.x = ex2(p.x - M.x); p.y = ex2(p.y - M.y); p.z = ex2(p.z - M.z); p.w = ex2(p.w - M.w);
                const float4 l = p;
                p.x *= vs; p.y *= vs; p.z *= vs; p.w *= vs;
                const float4 hi = make_float4(tf32_trunc(p.x), tf32_trunc(p.y), tf32_trunc(p.z), tf32_trunc(p.w));
                const float4 lo = make_float4(tf32_trunc(p.x - hi.x), tf32_trunc(p.y - hi.y), tf32_trunc(p.z - hi.z), tf32_trunc(p.w - hi.w));
                const float4 z = make_float4((hi.x + lo.x) * vz, (hi.y + lo.y) * vz, (hi.z + lo.z) * vz, (hi.w + lo.w) * vz);
                {
                    float* pb = (float*)(smem + OFF_PB) + (i * NCW + warp) * 256 + (lane >> 4) * 128 + ((lane & 7) >> 1) * 4 +
                                ((lane >> 3) & 1) * 2 + (lane & 1);
                    pb[0 * 16] = hi.x; pb[1 * 16] = lo.x; pb[2 * 16] = hi.y; pb[3 * 16] = lo.y;
                    pb[4 * 16] = hi.z; pb[5 * 16] = lo.z; pb[6 * 16] = hi.w; pb[7 * 16] = lo.w;
                }
                const bool b4 = lane & 16, b3 = lane & 8;
                const float u0 = (b4 ? z.x : l.x) + __shfl_xor_sync(0xffffffffu, b4 ? l.x : z.x, 16);
                const float u1 = (b4 ? z.y : l.y) + __shfl_xor_sync(0xffffffffu, b4 ? l.y : z.y, 16);
                const float u2 = (b4 ? z.z : l.z) + __shfl_xor_sync(0xffffffffu, b4 ? l.z : z.z, 16);
                const float u3 = (b4 ? z.w : l.w) + __shfl_xor_sync(0xffffffffu, b4 ? l.w : z.w, 16);
                const float v0 = (b3 ? u2 : u0) + __shfl_xor_sync(0xffffffffu, b3 ? u0 : u2, 8);
                const float v1 = (b3 ? u3 : u1) + __shfl_xor_sync(0xffffffffu, b3 ? u1 : u3, 8);
                float t = (b2 ? v1 : v0) + __shfl_xor_sync(0xffffffffu, b2 ? v0 : v1, 4);
                t += __shfl_xor_sync(0xffffffffu, t, 2);
                t += __shfl_xor_sync(0xffffffffu, t, 1);
                if (!(lane & 3)) s_wsz[(i * NCW + warp) * 8 + (lane >> 2)] = t;
                const float wv = fabsf(vs) * (16.f + fabsf(vz));
                const float y0 = (b4 ? l.z : l.x) * wv + __shfl_xor_sync(0xffffffffu, (b4 ? l.x : l.z) * wv, 16);
                const float y1 = (b4 ? l.w : l.y) * wv + __shfl_xor_sync(0xffffffffu, (b4 ? l.y : l.w) * wv, 16);
                float y = (b3 ? y1 : y0) + __shfl_xor_sync(0xffffffffu, b3 ? y0 : y1, 8);
#pragma unroll
                for (int o = 4; o > 0; o >>= 1) y += __shfl_xor_sync(0xffffffffu, y, o);
                if (!(lane & 7)) ((float*)(smem + OFF_WB))[(i * NCW + warp) * REP + (lane >> 3)] = y;
                __syncwarp();
                if (lane == 0) mbar_arrive(bar_own + i * 8);
            }
        }
    }

    const int g = lane >> 2, t = lane & 3;
    const int oidx = t * DH + warp * 16 + g * 2;
    unsigned long long* pacc = &g_acc[((tid / BLK) * ACC_STRIDE + head0) * BLK + tid % BLK];
    __nv_bfloat162* pout = (__nv_bfloat162*)(out + head0 * (REP * DH) + oidx);
    const uint32_t piece = (warp & 1) * 4 + (g >> 1);
    const uint32_t xoff0 = sb + OFF_RING + (warp >> 1) * 4096 + (2 * t) * 128 + ((piece ^ (2 * t)) << 4) + (g & 1) * 8;
    const uint32_t xoff1 = sb + OFF_RING + (warp >> 1) * 4096 + (2 * t + 1) * 128 + ((piece ^ (2 * t + 1)) << 4) + (g & 1) * 8;
    uint32_t pa = sb + OFF_PB + lane * 16;
    const uint32_t vbar = (warp >> 1) == 3 ? bar_full : bar_vfull + (warp >> 1) * (STAGES * 8);
    static_assert(NCH % (2 * STAGES) == 0, "phase V starts at stage 0, parity 0");
#pragma unroll 1
    for (int seg = 0; seg < HPG; seg++) {
        mbar_wait(bar_own + seg * 8, 0);
        float zc = 0.f;
#pragma unroll
        for (int c = 0; c < CPS; c++) zc += s_wsz[(seg * CPS + c) * 8 + 4 + t];
        float d0[4] = {-0.5f * zc, 0.f, -0.5f * zc, 0.f}, d1[4] = {-0.5f * zc, 0.f, -0.5f * zc, 0.f};
        float4 fz;
#pragma unroll 1
        for (int c = 0; c < CPS; c++) {
            const float4 pA = lds_f4(pa), pB = lds_f4(pa + 512);
            pa += 1024;
            uint32_t xa0 = xoff0 + st * CHUNK_BYTES, xa1 = xoff1 + st * CHUNK_BYTES;
            asm volatile("" : "+r"(xa0), "+r"(xa1));
            if (c == FWAIT) {
                mbar_wait(bar_fready + seg * 8, 0);
                fz = lds_f4(sb + OFF_F + (seg * REP + t) * 16);
            }
            mbar_wait(vbar + st * 8, ph);
            int2 x[4][2];
#pragma unroll
            for (int s = 0; s < 4; s++) {
                x[s][0] = lds_i2(xa0 + s * 1024);
                x[s][1] = lds_i2(xa1 + s * 1024);
            }
            __syncwarp();
            if (lane == 0) mbar_arrive(bar_empty + st * 8);
            mma_tf32(d0, (float)x[0][0].x, (float)x[0][0].y, (float)x[0][1].x, (float)x[0][1].y, pA.x, pA.y);
            mma_tf32(d1, (float)x[1][0].x, (float)x[1][0].y, (float)x[1][1].x, (float)x[1][1].y, pA.z, pA.w);
            mma_tf32(d0, (float)x[2][0].x, (float)x[2][0].y, (float)x[2][1].x, (float)x[2][1].y, pB.x, pB.y);
            mma_tf32(d1, (float)x[3][0].x, (float)x[3][0].y, (float)x[3][1].x, (float)x[3][1].y, pB.z, pB.w);
            if (++st == STAGES) { st = 0; ph ^= 1; }
        }
        const float ox = (d0[0] + d0[1]) + (d1[0] + d1[1]);
        const float oy = (d0[2] + d0[3]) + (d1[2] + d1[3]);
        const float ya = ox * fz.x, yb = oy * fz.x;
        unsigned long long op = ((unsigned long long)(long long)__float2int_rn(ya) << 39) +
                                ((unsigned long long)(long long)__float2int_rn(yb) << 14) + 1ull;
        const bool wide = !(fabsf(ya) <= fz.y) | !(fabsf(yb) <= fz.y);
        unsigned long long tot = 0ull;
        asm volatile("{\n.reg .pred p;\nsetp.eq.u32 p, %3, 0;\n@p atom.relaxed.gpu.global.add.u64 %0, [%1], %2;\n}"
                     : "+l"(tot) : "l"(pacc), "l"(op), "r"((uint32_t)wide) : "memory");
        if (__builtin_expect(wide, 0)) op = wide_add(pacc, &g_wide[head0 + seg][oidx], ox * fz.w, oy * fz.w);
        tot += op;
        const int vb = (int)((long long)(tot << 25) >> 39);
        const int va = ((int)(tot >> 32) + 64) >> 7;
        const float oa = (float)va * fz.z, ob = (float)vb * fz.z;
        const uint32_t low = (uint32_t)tot & 0x3fffu;
        const __nv_bfloat162 o2 = __floats2bfloat162_rn(oa, ob);
        asm volatile("{\n.reg .pred p;\nsetp.eq.u32 p, %2, %3;\n@p st.global.u32 [%0], %1;\n}"
                     ::"l"(pout), "r"(*(const uint32_t*)&o2), "r"(low), "n"(CPG) : "memory");
        if (__builtin_expect(low > CPG && (low & 127u) == CPG, 0)) wide_finish(pout, &g_wide[head0 + seg][oidx], oa, ob);
        pacc += BLK;
        pout += REP * DH / 2;
    }
}

}

typedef CUresult (*EncodeTiledFn)(CUtensorMap*, CUtensorMapDataType, cuuint32_t, void*, const cuuint64_t*, const cuuint64_t*,
                                  const cuuint32_t*, const cuuint32_t*, CUtensorMapInterleave, CUtensorMapSwizzle,
                                  CUtensorMapL2promotion, CUtensorMapFloatOOBfill);

extern "C" void kernel_launch(void* const* d_in, const int* in_sizes, int n_in, void* d_out, int out_size) {
    (void)in_sizes; (void)n_in; (void)out_size;
    static int tau = -1;
    static EncodeTiledFn encode = nullptr;
    if (tau < 0) {
        cudaFuncSetAttribute(kvq_decode_kernel, cudaFuncAttributeMaxDynamicSharedMemorySize, SMEM_BYTES);
        int dev = 0, khz = 0, bits = 0;
        cudaGetDevice(&dev);
        cudaDeviceGetAttribute(&khz, cudaDevAttrMemoryClockRate, dev);
        cudaDeviceGetAttribute(&bits, cudaDevAttrGlobalMemoryBusWidth, dev);
        const double bytes_per_ns = 2.0 * khz * 1e-6 * (bits / 8);
        tau = bytes_per_ns > 0.0 ? (int)((double)NCTA * CHUNK_BYTES / (bytes_per_ns * TAU_EFF)) : 0;
        void* fn = nullptr;
        cudaDriverEntryPointQueryResult qr;
        cudaGetDriverEntryPoint("cuTensorMapEncodeTiled", &fn, cudaEnableDefault, &qr);
        encode = (EncodeTiledFn)fn;
    }
    if (!encode) return;
    CUtensorMap vmap;
    const cuuint64_t dims[2] = {DH, (cuuint64_t)HKV * SKV}, strides[1] = {DH * 4};
    const cuuint32_t box[2] = {32, CHUNK_TOK}, estr[2] = {1, 1};
    encode(&vmap, CU_TENSOR_MAP_DATA_TYPE_INT32, 2, d_in[2], dims, strides, box, estr, CU_TENSOR_MAP_INTERLEAVE_NONE,
           CU_TENSOR_MAP_SWIZZLE_128B, CU_TENSOR_MAP_L2_PROMOTION_NONE, CU_TENSOR_MAP_FLOAT_OOB_FILL_NONE);
    kvq_decode_kernel<<<NCTA, NTHREADS, SMEM_BYTES>>>(
        (const __nv_bfloat16*)d_in[0], (const int*)d_in[1], vmap, (const __nv_bfloat16*)d_in[3],
        (const __nv_bfloat16*)d_in[4], (const __nv_bfloat16*)d_in[5], (const __nv_bfloat16*)d_in[6],
        (__nv_bfloat16*)d_out, tau);
}
```
